```python
import torch

def _softmax(x, axis=-1):
    return torch.softmax(x, dim=axis)
def _gelu(x):
    return torch.nn.functional.gelu(x, approximate="tanh")
def _silu(x):
    return torch.nn.functional.silu(x)
def _sigmoid(x):
    return torch.sigmoid(x)
def _layernorm(x, axis=-1, eps=1e-5):
    m = x.mean(dim=axis, keepdim=True)
    v = x.var(dim=axis, keepdim=True, unbiased=False)
    return (x - m) / torch.sqrt(v + eps)
def _scatter_add(tgt, idx, src, axis=0):
    return tgt.clone().index_add_(axis, idx, src)
def _segment_sum(src, seg, n):
    out = torch.zeros((n,) + src.shape[1:], dtype=src.dtype)
    return out.index_add_(0, seg, src)
def _pad(x, pw):
    flat = tuple(v for pair in reversed(pw) for v in pair)
    return torch.nn.functional.pad(x, flat)

kernel_name = 'standalone__dense_activation_gelu__prompt'

def setup_inputs():

    _w = (lambda a: (lambda t: t.to(torch.bfloat16) if t.is_floating_point() else t)(torch.as_tensor(a)))
    B, S, D, F = 1, 2048, 512, 1376
    return {
        "x": _w((lambda *s: torch.randn(*s, dtype=torch.bfloat16) * 0.05)(B, S, D)),
        "w1": _w((lambda *s: torch.randn(*s, dtype=torch.bfloat16) * 3.2)(D, F) * (D ** -0.5)),
        "b1": _w((lambda *s: torch.randn(*s, dtype=torch.bfloat16) * 3.2)(F) * 0.01),
        "w2": _w((lambda *s: torch.randn(*s, dtype=torch.bfloat16) * 0.05)(F, D) * (F ** -0.5)),
        "b2": _w((lambda *s: torch.randn(*s, dtype=torch.bfloat16) * 0.1)(D) * 0.01),
    }

def reference(x, w1, b1, w2, b2):
    h = torch.einsum("bsd,df->bsf", x, w1) + b1
    h = _gelu(h)
    return torch.einsum("bsf,fd->bsd", h, w2) + b2
```

```cpp
#include <cuda_runtime.h>
#include <cuda_bf16.h>
#include <cuda.h>
#include <stdint.h>

namespace {

constexpr int kM = 2048, kD = 512, kF = 1376;
constexpr int kHP = 1408;
constexpr int kThreads = 384;
constexpr uint32_t kASlot = 16384, kBSlot = 8192;
constexpr uint32_t kOffA = 0, kOffB = 8 * kASlot, kOffStage = kOffB + 8 * kBSlot, kOffBar = kOffStage + 32768;
constexpr uint32_t kSmemBytes = kOffBar + 1024 + 1024;

__device__ __align__(1024) __nv_bfloat16 g_h[kM * kHP];
__device__ unsigned g_flags[16 * 3 * 8];
__device__ unsigned g_done;
#define PROF(i) do {} while (0)
#define PROFW(i) do {} while (0)
#define PARGS
#define PPASS

__device__ __forceinline__ uint32_t smem_u32(const void* p) { return (uint32_t)__cvta_generic_to_shared(p); }
__device__ __forceinline__ void mbar_init(uint32_t bar, uint32_t cnt) {
  asm volatile("mbarrier.init.shared::cta.b64 [%0], %1;" ::"r"(bar), "r"(cnt) : "memory");
}
__device__ __forceinline__ void mbar_expect_tx(uint32_t bar, uint32_t bytes) {
  asm volatile("mbarrier.arrive.expect_tx.shared::cta.b64 _, [%0], %1;" ::"r"(bar), "r"(bytes) : "memory");
}
__device__ __forceinline__ void mbar_arrive(uint32_t bar) {
  asm volatile("mbarrier.arrive.shared::cta.b64 _, [%0];" ::"r"(bar) : "memory");
}
__device__ __forceinline__ void mbar_wait(uint32_t bar, uint32_t parity) {
  uint32_t ok;
#pragma unroll 1
  for (uint32_t i = 0; i < (1u << 22); i++) {
    asm volatile("{\n.reg .pred p;\nmbarrier.try_wait.parity.shared::cta.b64 p, [%1], %2;\nselp.u32 %0, 1, 0, p;\n}"
                 : "=r"(ok) : "r"(bar), "r"(parity) : "memory");
    if (ok) return;
  }
  __trap();
}
__device__ __forceinline__ bool mbar_test(uint32_t bar, uint32_t parity) {
  uint32_t ok;
  asm volatile("{\n.reg .pred p;\nmbarrier.test_wait.parity.shared::cta.b64 p, [%1], %2;\nselp.u32 %0, 1, 0, p;\n}"
               : "=r"(ok) : "r"(bar), "r"(parity) : "memory");
  return ok;
}
__device__ __forceinline__ bool elect_one() {
  uint32_t pred;
  asm volatile("{\n.reg .pred p;\nelect.sync _|p, 0xffffffff;\nselp.u32 %0, 1, 0, p;\n}" : "=r"(pred));
  return pred;
}
__device__ __forceinline__ void tma_load(uint32_t dst, const CUtensorMap* map, uint32_t bar, int c0, int c1) {
  asm volatile("cp.async.bulk.tensor.2d.shared::cluster.global.mbarrier::complete_tx::bytes [%0], [%1, {%3, %4}], [%2];"
               ::"r"(dst), "l"(map), "r"(bar), "r"(c0), "r"(c1) : "memory");
}
__device__ __forceinline__ void tma_load_pair(uint32_t dst, const CUtensorMap* map, uint32_t bar, int c0, int c1) {
  asm volatile("cp.async.bulk.tensor.2d.shared::cluster.global.mbarrier::complete_tx::bytes.multicast::cluster [%0], [%1, {%3, %4}], [%2], %5;"
               ::"r"(dst), "l"(map), "r"(bar), "r"(c0), "r"(c1), "h"((uint16_t)3) : "memory");
}
__device__ __forceinline__ void mbar_arrive_remote(uint32_t cluster_addr) {
  asm volatile("mbarrier.arrive.shared::cluster.b64 _, [%0];" ::"r"(cluster_addr) : "memory");
}
__device__ __forceinline__ void cluster_arrive() { asm volatile("barrier.cluster.arrive.relaxed.aligned;" ::: "memory"); }
__device__ __forceinline__ void cluster_wait() { asm volatile("barrier.cluster.wait.aligned;" ::: "memory"); }
__device__ __forceinline__ void tma_store(const CUtensorMap* map, uint32_t src, int c0, int c1) {
  asm volatile("cp.async.bulk.tensor.2d.global.shared::cta.bulk_group [%0, {%2, %3}], [%1];"
               ::"l"(map), "r"(src), "r"(c0), "r"(c1) : "memory");
}
__device__ __forceinline__ void bar_sync(int id, int n) { asm volatile("bar.sync %0, %1;" ::"r"(id), "r"(n) : "memory"); }
__device__ __forceinline__ void bar_arrive(int id, int n) { asm volatile("bar.arrive %0, %1;" ::"r"(id), "r"(n) : "memory"); }
__device__ __forceinline__ void wg_fence() { asm volatile("wgmma.fence.sync.aligned;" ::: "memory"); }
__device__ __forceinline__ void wg_commit() { asm volatile("wgmma.commit_group.sync.aligned;" ::: "memory"); }
template <int N> __device__ __forceinline__ void wg_wait() { asm volatile("wgmma.wait_group.sync.aligned %0;" ::"n"(N) : "memory"); }
__device__ __forceinline__ void fence_acc(float (&d)[64]) {
#pragma unroll
  for (int i = 0; i < 64; i++) asm volatile("" : "+f"(d[i])::"memory");
}
__device__ __forceinline__ uint64_t make_desc(uint32_t addr) {
  return (uint64_t)((addr & 0x3FFFF) >> 4) | ((uint64_t)1 << 16) | ((uint64_t)(1024 >> 4) << 32) | ((uint64_t)1 << 62);
}

__device__ __forceinline__ void wgmma_t128(float (&d)[64], uint64_t da, uint64_t db, uint32_t scale_d) {
  asm volatile("{\n.reg .pred p;\nsetp.ne.b32 p, %66, 0;\n"
    "wgmma.mma_async.sync.aligned.m64n128k16.f32.bf16.bf16 "
    "{%0, %1, %2, %3, %4, %5, %6, %7, %8, %9, %10, %11, %12, %13, %14, %15, %16, %17, %18, %19, %20, %21, %22, %23, %24, %25, %26, %27, %28, %29, %30, %31, %32, %33, %34, %35, %36, %37, %38, %39, %40, %41, %42, %43, %44, %45, %46, %47, %48, %49, %50, %51, %52, %53, %54, %55, %56, %57, %58, %59, %60, %61, %62, %63}, "
    "%64, %65, p, 1, 1, 1, 0;\n}\n"
    : "+f"(d[0]), "+f"(d[1]), "+f"(d[2]), "+f"(d[3]), "+f"(d[4]), "+f"(d[5]), "+f"(d[6]), "+f"(d[7]), "+f"(d[8]), "+f"(d[9]), "+f"(d[10]), "+f"(d[11]), "+f"(d[12]), "+f"(d[13]), "+f"(d[14]), "+f"(d[15]), "+f"(d[16]), "+f"(d[17]), "+f"(d[18]), "+f"(d[19]), "+f"(d[20]), "+f"(d[21]), "+f"(d[22]), "+f"(d[23]), "+f"(d[24]), "+f"(d[25]), "+f"(d[26]), "+f"(d[27]), "+f"(d[28]), "+f"(d[29]), "+f"(d[30]), "+f"(d[31]), "+f"(d[32]), "+f"(d[33]), "+f"(d[34]), "+f"(d[35]), "+f"(d[36]), "+f"(d[37]), "+f"(d[38]), "+f"(d[39]), "+f"(d[40]), "+f"(d[41]), "+f"(d[42]), "+f"(d[43]), "+f"(d[44]), "+f"(d[45]), "+f"(d[46]), "+f"(d[47]), "+f"(d[48]), "+f"(d[49]), "+f"(d[50]), "+f"(d[51]), "+f"(d[52]), "+f"(d[53]), "+f"(d[54]), "+f"(d[55]), "+f"(d[56]), "+f"(d[57]), "+f"(d[58]), "+f"(d[59]), "+f"(d[60]), "+f"(d[61]), "+f"(d[62]), "+f"(d[63])
    : "l"(da), "l"(db), "r"(scale_d));
}

__device__ __forceinline__ uint32_t pack_bf16(float lo, float hi) {
  uint32_t r;
  asm("cvt.rn.bf16x2.f32 %0, %1, %2;" : "=r"(r) : "f"(hi), "f"(lo));
  return r;
}
__device__ __forceinline__ void stmatrix_x4_trans(uint32_t addr, uint32_t r0, uint32_t r1, uint32_t r2, uint32_t r3) {
  asm volatile("stmatrix.sync.aligned.m8n8.x4.trans.shared.b16 [%0], {%1, %2, %3, %4};" ::"r"(addr), "r"(r0), "r"(r1), "r"(r2), "r"(r3) : "memory");
}
__device__ __forceinline__ uint4 lds128(uint32_t addr) {
  uint4 v;
  asm volatile("ld.shared.v4.b32 {%0, %1, %2, %3}, [%4];" : "=r"(v.x), "=r"(v.y), "=r"(v.z), "=r"(v.w) : "r"(addr) : "memory");
  return v;
}
__device__ __forceinline__ void sts128f(uint32_t addr, float a, float b, float c, float d) {
  asm volatile("st.shared.v4.f32 [%0], {%1, %2, %3, %4};" ::"r"(addr), "f"(a), "f"(b), "f"(c), "f"(d) : "memory");
}
__device__ __forceinline__ float gelu2(float v, float k1) {
  float p = fmaf(v * v, k1, 0.7978845608028654f);
  float t;
  asm("tanh.approx.f32 %0, %1;" : "=f"(t) : "f"(v * p));
  return fmaf(v, t, v);
}
__device__ __forceinline__ float lds_bf16(uint32_t addr) {
  uint32_t v;
  asm volatile("ld.shared.u16 %0, [%1];" : "=r"(v) : "r"(addr) : "memory");
  return __uint_as_float(v << 16);
}

__device__ __forceinline__ void release_slot(uint32_t bar, uint32_t peer_bar, int s, bool pred, bool pred_a) {
  if (pred_a) mbar_arrive(bar + 256 + s * 8);
  if (pred) { mbar_arrive(bar + 64 + s * 8); mbar_arrive_remote(peer_bar + 64 + s * 8); }
}
__device__ __forceinline__ void mma_round(float (&acc)[64], uint64_t dw, uint64_t dx, uint32_t bar, uint32_t peer_bar, uint32_t parity,
                                          uint32_t& ok, int nblk, uint32_t accumulate, bool rel_lo, bool rel_hi, bool rel_a,
                                          bool short_last, int prof_it PARGS) {
#pragma unroll
  for (int s = 0; s < 8; s++) {
    if (s >= 6 && s >= nblk) break;
    if (!ok) mbar_wait(bar + s * 8, parity);
    const uint64_t w = dw + s * (kBSlot >> 4), x = dx + s * (kASlot >> 4);
    if (s == 7 && short_last) {
      wg_fence();
      wgmma_t128(acc, w, x, 1u);
      wgmma_t128(acc, w + 128, x + 2, 1u);
      wg_commit();
    } else {
      wg_fence();
      wgmma_t128(acc, w, x, s == 0 ? accumulate : 1u);
      wgmma_t128(acc, w + 128, x + 2, 1u);
      wgmma_t128(acc, w + 256, x + 4, 1u);
      wgmma_t128(acc, w + 384, x + 6, 1u);
      wg_commit();
    }
    {
      const bool rel = s < 2 ? rel_lo : rel_hi;
      release_slot(bar, peer_bar, (s + 6) & 7, rel, rel && rel_a);
    }
    ok = mbar_test(bar + ((s + 1) & 7) * 8, s == 7 ? parity ^ 1u : parity);
    wg_wait<1>();
  }
}

__device__ __forceinline__ uint32_t stage_addr(uint32_t tile, int w, int lane) {
  const int m = lane >> 3, r7 = lane & 7;
  return tile + ((m >> 1) * 8 + r7) * 128 + (((2 * w + (m & 1)) ^ r7) << 4);
}
__device__ __forceinline__ void stage_tile(const uint32_t (&p)[32], uint32_t tile, int w, int lane) {
  const uint32_t a = stage_addr(tile, w, lane);
#pragma unroll
  for (int gp = 0; gp < 8; gp++) stmatrix_x4_trans(a + gp * 2048, p[4 * gp], p[4 * gp + 1], p[4 * gp + 2], p[4 * gp + 3]);
}

__global__ void __cluster_dims__(2, 1, 1) __launch_bounds__(kThreads, 1)
ffn_fused_kernel(const __nv_bfloat16* __restrict__ b1, const __nv_bfloat16* __restrict__ b2,
                 __nv_bfloat16* __restrict__ out, const uint8_t* __restrict__ w1_raw, const uint8_t* __restrict__ w2_raw,
                 const __grid_constant__ CUtensorMap mX, const __grid_constant__ CUtensorMap mW1,
                 const __grid_constant__ CUtensorMap mW1h, const __grid_constant__ CUtensorMap mH,
                 const __grid_constant__ CUtensorMap mHq, const __grid_constant__ CUtensorMap mW2h) {
  extern __shared__ uint8_t smem_raw[];
  uint32_t base = (smem_u32(smem_raw) + 1023u) & ~1023u;
  asm volatile("mov.u32 %0, %0;" : "+r"(base));
  const uint32_t sA = base + kOffA, sB = base + kOffB, sStage = base + kOffStage;
  const uint32_t bar_full = base + kOffBar, bar_empty = bar_full + 64;
  const uint32_t bar_staged = bar_full + 128;
  const uint32_t bar_stfree = bar_full + 224;
  const uint32_t bar_bias = bar_full + 232;
  const uint32_t bar_emptyA = bar_full + 256;
  const uint32_t sBias = bar_full + 320;
  const uint32_t bar_hf = bar_full + 832;
  const int warp = __shfl_sync(0xffffffff, threadIdx.x >> 5, 0);
  const int lane = threadIdx.x & 31;

  int grp, j;
  {
    const int c = blockIdx.x >> 1;
    int gpc;
    if (c < 4) { gpc = 0; j = 4 + c; }
    else if (c < 36) { gpc = (c - 4) & 7; j = (c - 4) >> 3; }
    else { gpc = 1 + (c - 36) % 7; j = 4 + (c - 36) / 7; }
    grp = 2 * gpc + (blockIdx.x & 1);
  }
  const int row0 = grp * 128;
  const uint32_t rank = blockIdx.x & 1;

  if (warp == 8) {
    const int wcol = 192 * j;
    if (elect_one()) {
#pragma unroll
      for (int i = 0; i < 8; i++) mbar_init(bar_full + i * 8, 1);
      asm volatile("fence.proxy.async.shared::cta;" ::: "memory");
      mbar_expect_tx(bar_full, kASlot + kBSlot);
      tma_load(sA, &mX, bar_full, 0, row0);
      tma_load(sB, &mW1, bar_full, wcol, 0);
#pragma unroll
      for (int i = 0; i < 8; i++) mbar_init(bar_empty + i * 8, 8);
#pragma unroll
      for (int i = 0; i < 6; i++) mbar_init(bar_staged + i * 8, 4);
      mbar_init(bar_stfree, 1);
      mbar_init(bar_bias, 1);
#pragma unroll
      for (int i = 0; i < 8; i++) mbar_init(bar_emptyA + i * 8, 4);
#pragma unroll
      for (int i = 0; i < 24; i++) mbar_init(bar_hf + i * 8, 1);
      asm volatile("fence.mbarrier_init.release.cluster;" ::: "memory");
    }
    __syncwarp();
    bar_arrive(1, kThreads - 32);
    bar_arrive(6, 64);
    cluster_arrive();
    PROF(0);
    if (elect_one()) {
#pragma unroll
      for (int kb = 1; kb < 8; kb++) {
        mbar_expect_tx(bar_full + kb * 8, kASlot + kBSlot);
        tma_load(sA + kb * kASlot, &mX, bar_full + kb * 8, kb * 64, row0);
        tma_load(sB + kb * kBSlot, &mW1, bar_full + kb * 8, wcol, kb * 64);
      }
    }
    __syncwarp();
    cluster_wait();
    PROF(1);
#pragma unroll 1
    for (int it = 8; it < 24; it++) {
      const int s = it & 7, t = it >> 3;
      mbar_wait(bar_empty + s * 8, (t - 1) & 1);
      if (elect_one()) {
        mbar_expect_tx(bar_full + s * 8, kBSlot);
        tma_load_pair(sB + s * kBSlot + rank * 4096, &mW1h, bar_full + s * 8, wcol + 64 * t, s * 64 + rank * 32);
      }
      __syncwarp();
      PROF(160 + it);
    }
    PROF(2);
    {
      uint32_t off = 0, par = 0;
      int col = rank * 32;
#pragma unroll 1
      for (int q = 0; q < 22; q++) {
        if (q == 8) col = 64 + rank * 32;
        if (q == 15) col = 128 + rank * 32;
        mbar_wait(bar_empty + off, par);
        if (elect_one()) {
          mbar_expect_tx(bar_full + off, kASlot + kBSlot);
          tma_load_pair(sB + off * (kBSlot / 8) + rank * 4096, &mW2h, bar_full + off, j * 64, col);
        }
        __syncwarp();
        col += 192;
        off += 8;
        if (off == 64) { off = 0; par ^= 1; }
      }
    }
    PROF(6);
  } else if (warp == 9) {
    cluster_arrive();
    bar_sync(1, kThreads - 32);
    cluster_wait();
    uint32_t off = 0, par = 0;
#pragma unroll 1
    for (int t = 0; t < 3; t++) {
      const int nq = t == 0 ? 8 : 7;
      int col = t * 64;
#pragma unroll 1
      for (int i = 0; i < nq; i++) {
        mbar_wait(bar_hf + (t * 8 + i) * 8, 0);
        if (i == 0) PROF(3 + t);
        mbar_wait(bar_emptyA + off, par);
        if (elect_one()) {
          asm volatile("fence.proxy.async.global;" ::: "memory");
          tma_load(sA + off * (kASlot / 8), &mH, bar_full + off, col, row0);
        }
        __syncwarp();
        PROF(184 + i + (t == 0 ? 0 : (t == 1 ? 8 : 15)));
        col += 192;
        off += 8;
        if (off == 64) { off = 0; par ^= 1; }
      }
    }
  } else if (warp == 11) {
    cluster_arrive();
    bar_sync(1, kThreads - 32);
    cluster_wait();
    unsigned done;
    asm volatile("ld.relaxed.gpu.global.u32 %0, [%1];" : "=r"(done) : "l"(&g_done) : "memory");
    const unsigned target = (done >> 7) + 1u;
#pragma unroll 1
    for (int t = 0; t < 3; t++) {
      const uint32_t want = t == 0 ? 0xffu : 0x7fu;
      const unsigned* f = &g_flags[(grp * 3 + t) * 8 + (lane & 7)];
      uint32_t seen = 0;
      unsigned v0, v1;
      asm volatile("ld.relaxed.gpu.global.u32 %0, [%1];" : "=r"(v0) : "l"(f) : "memory");
      __nanosleep(60);
      asm volatile("ld.relaxed.gpu.global.u32 %0, [%1];" : "=r"(v1) : "l"(f) : "memory");
#pragma unroll 1
      for (uint32_t spins = 0;; spins++) {
        uint32_t m = __ballot_sync(0xffffffff, (int)(v0 - target) >= 0) & want;
        if (lane < 8 && (((m & ~seen) >> lane) & 1u)) mbar_arrive(bar_hf + (t * 8 + lane) * 8);
        seen |= m;
        if (seen == want) break;
        asm volatile("ld.relaxed.gpu.global.u32 %0, [%1];" : "=r"(v0) : "l"(f) : "memory");
        m = __ballot_sync(0xffffffff, (int)(v1 - target) >= 0) & want;
        if (lane < 8 && (((m & ~seen) >> lane) & 1u)) mbar_arrive(bar_hf + (t * 8 + lane) * 8);
        seen |= m;
        if (seen == want) break;
        asm volatile("ld.relaxed.gpu.global.u32 %0, [%1];" : "=r"(v1) : "l"(f) : "memory");
        if (spins > (1u << 20)) __trap();
      }
    }
  } else if (warp == 10) {
    cluster_arrive();
    {
      uint32_t v[4];
#pragma unroll
      for (int i = 0; i < 3; i++) {
        const int c = 192 * j + 64 * i + 2 * lane;
        v[i] = c < kF ? __ldg(reinterpret_cast<const uint32_t*>(b1 + c)) : 0u;
      }
      v[3] = __ldg(reinterpret_cast<const uint32_t*>(b2 + j * 64 + 2 * lane));
#pragma unroll
      for (int i = 0; i < 4; i++) asm volatile("st.shared.u32 [%0], %1;" ::"r"(sBias + i * 128 + lane * 4), "r"(v[i]) : "memory");
      bar_sync(6, 64);
      if (lane == 0) mbar_arrive(bar_bias);
    }
    cluster_wait();
    mbar_wait(bar_full + 7 * 8, 0);
    if (elect_one()) {
      constexpr uint32_t kShare = kD * kF * 2 / 128;
      asm volatile("cp.async.bulk.prefetch.L2.global [%0], %1;" ::"l"(w1_raw + blockIdx.x * kShare), "r"(kShare) : "memory");
      asm volatile("cp.async.bulk.prefetch.L2.global [%0], %1;" ::"l"(w2_raw + blockIdx.x * kShare), "r"(kShare) : "memory");
    }
    __syncwarp();
    const int nt = j < 7 ? 3 : 1;
#pragma unroll 1
    for (int t = 0; t < nt; t++) {
#pragma unroll 1
      for (int hf = 0; hf < 2; hf++) {
        mbar_wait(bar_staged + (t * 2 + hf) * 8, 0);
        if (t < 2) PROF(40 + t * 8 + hf);
        if (elect_one()) {
          tma_store(&mHq, sStage + (t & 1) * 16384 + hf * 8192, (3 * j + t) * 64, row0 + hf * 64);
          asm volatile("cp.async.bulk.commit_group;" ::: "memory");
        }
        __syncwarp();
      }
      if (t < 2) PROF(44 + t * 8);
      if (elect_one()) {
        asm volatile("cp.async.bulk.wait_group 0;" ::: "memory");
        asm volatile("red.relaxed.gpu.global.add.u32 [%0], 1;" ::"l"(&g_flags[(grp * 3 + t) * 8 + j]) : "memory");
        if (t == 0) mbar_arrive(bar_stfree);
      }
      __syncwarp();
      PROF(36 + t);
    }
  } else {
    const int wg = warp >> 2, w = warp & 3;
    const int my_turn = wg ? 2 : 3, other_turn = wg ? 3 : 2;
    const bool leader = lane == 0;
    float acc[64];
    const uint64_t dx0 = make_desc(sA), dw0 = make_desc(sB);
    const int mcol = 16 * w + (lane >> 2);
    uint32_t peer_bar;
    asm volatile("mapa.shared::cluster.u32 %0, %1, %2;" : "=r"(peer_bar) : "r"(bar_full), "r"(rank ^ 1));
    cluster_arrive();
    bar_sync(1, kThreads - 32);
    cluster_wait();
    const uint32_t zero = blockIdx.y;
#pragma unroll 1
    for (int round = wg; round < 4; round += 2) {
      uint32_t accumulate = 0u;
      if (round < 3) {
        mbar_wait(bar_bias, 0);
        const float c0 = lds_bf16(sBias + round * 128 + mcol * 2), c1 = lds_bf16(sBias + round * 128 + mcol * 2 + 16);
#pragma unroll
        for (int g = 0; g < 16; g++) { acc[4 * g] = c0; acc[4 * g + 1] = c0; acc[4 * g + 2] = c1; acc[4 * g + 3] = c1; }
        accumulate = 1u;
      }
      fence_acc(acc);
      if (round > 0) bar_sync(my_turn, 256);
      PROF(8 + 3 * round);
      uint32_t ok = 0;
      const int last = round == 3 ? 5 : round;
#pragma unroll 1
      for (int rr = round; rr <= last; rr++) {
        mma_round(acc, dw0, dx0, bar_full, peer_bar, rr & 1, ok, rr == 5 ? 6 : 8, accumulate, leader && rr == 4, leader && rr != 5,
                  rr >= 2, rr == 3, rr * 8 PPASS);
        accumulate = 1u;
      }
      if (round < 3) {
        bar_arrive(other_turn, 256);
        release_slot(bar_full, peer_bar, 6, leader, leader && round == 2);
      }
      wg_wait<0>();
      fence_acc(acc);
      if (round < 3) release_slot(bar_full, peer_bar, 7, leader, leader && round == 2);
      PROF(9 + 3 * round);
      if (round == 1) PROF(56 + w);
      if (round == 3) break;
      if (round == 2) mbar_wait(bar_stfree, 0);
      const uint32_t sa = stage_addr(sStage + wg * 16384, w, lane);
      uint32_t dep = 0;
#pragma unroll
      for (int gp = 0; gp < 8; gp++) {
        const float k1 = __uint_as_float(__float_as_uint(0.035677408136300125f) | (dep & zero));
        uint32_t p[4];
#pragma unroll
        for (int h = 0; h < 2; h++) {
          const int g = 2 * gp + h;
          p[2 * h] = pack_bf16(gelu2(acc[4 * g], k1), gelu2(acc[4 * g + 1], k1));
          p[2 * h + 1] = pack_bf16(gelu2(acc[4 * g + 2], k1), gelu2(acc[4 * g + 3], k1));
        }
        dep = p[3];
        if (gp == 4) {
          asm volatile("fence.proxy.async.shared::cta;" ::: "memory");
          __syncwarp();
          if (leader) mbar_arrive(bar_staged + round * 16);
        }
        stmatrix_x4_trans(sa + gp * 2048, p[0], p[1], p[2], p[3]);
        __syncwarp();
      }
      asm volatile("fence.proxy.async.shared::cta;" ::: "memory");
      __syncwarp();
      if (leader) mbar_arrive(bar_staged + round * 16 + 8);
      PROF(10 + 3 * round);
      if (round == 1) PROF(52 + w);
    }
    if (wg == 1) {
      const float bias0 = lds_bf16(sBias + 384 + mcol * 2), bias1 = lds_bf16(sBias + 384 + mcol * 2 + 16);
      const uint32_t otile = sA + 7 * kASlot;
      const uint32_t sa = stage_addr(otile, w, lane);
#pragma unroll
      for (int gp = 0; gp < 8; gp++) {
        uint32_t p[4];
#pragma unroll
        for (int h = 0; h < 2; h++) {
          const int g = 2 * gp + h;
          p[2 * h] = pack_bf16(fmaf(acc[4 * g], 0.5f, bias0), fmaf(acc[4 * g + 1], 0.5f, bias0));
          p[2 * h + 1] = pack_bf16(fmaf(acc[4 * g + 2], 0.5f, bias1), fmaf(acc[4 * g + 3], 0.5f, bias1));
        }
        stmatrix_x4_trans(sa + gp * 2048, p[0], p[1], p[2], p[3]);
      }
      bar_sync(4, 128);
      const int t = threadIdx.x & 127, ch = t & 7;
      __nv_bfloat16* optr = out + (size_t)(row0 + (t >> 3)) * kD + j * 64 + ch * 8;
#pragma unroll
      for (int i = 0; i < 8; i++) {
        const int row = 16 * i + (t >> 3);
        const uint4 v = lds128(otile + row * 128 + ((ch ^ (row & 7)) << 4));
        *reinterpret_cast<uint4*>(optr + (size_t)i * 16 * kD) = v;
      }
      PROF(30);
      if (t == 0) asm volatile("red.relaxed.gpu.global.add.u32 [%0], 1;" ::"l"(&g_done) : "memory");
    }
  }
}

typedef CUresult (*EncodeTiledFn)(CUtensorMap*, CUtensorMapDataType, cuuint32_t, void*, const cuuint64_t*, const cuuint64_t*,
                                  const cuuint32_t*, const cuuint32_t*, CUtensorMapInterleave, CUtensorMapSwizzle,
                                  CUtensorMapL2promotion, CUtensorMapFloatOOBfill);

void encode_2d(EncodeTiledFn fn, CUtensorMap* m, const void* ptr, uint64_t cols, uint64_t rows, uint32_t box_cols, uint32_t box_rows) {
  cuuint64_t dims[2] = {cols, rows};
  cuuint64_t strides[1] = {cols * 2};
  cuuint32_t box[2] = {box_cols, box_rows};
  cuuint32_t es[2] = {1, 1};
  fn(m, CU_TENSOR_MAP_DATA_TYPE_BFLOAT16, 2, const_cast<void*>(ptr), dims, strides, box, es, CU_TENSOR_MAP_INTERLEAVE_NONE,
     CU_TENSOR_MAP_SWIZZLE_128B, CU_TENSOR_MAP_L2_PROMOTION_L2_128B, CU_TENSOR_MAP_FLOAT_OOB_FILL_NONE);
}

}

extern "C" void kernel_launch(void* const* d_in, const int* in_sizes, int n_in, void* d_out, int out_size) {
  (void)in_sizes; (void)n_in; (void)out_size;
  static CUtensorMap mX, mW1, mW1h, mH, mHq, mW2h;
  static const void* cached[3] = {nullptr, nullptr, nullptr};
  static bool init = false;
  if (!init || cached[0] != d_in[0] || cached[1] != d_in[1] || cached[2] != d_in[3]) {
    void* fnp = nullptr;
    cudaDriverEntryPointQueryResult st;
    cudaGetDriverEntryPoint("cuTensorMapEncodeTiled", &fnp, cudaEnableDefault, &st);
    EncodeTiledFn fn = (EncodeTiledFn)fnp;
    void* hptr = nullptr;
    cudaGetSymbolAddress(&hptr, g_h);
    encode_2d(fn, &mX, d_in[0], kD, kM, 64, 128);
    encode_2d(fn, &mW1, d_in[1], kF, kD, 64, 64);
    encode_2d(fn, &mW1h, d_in[1], kF, kD, 64, 32);
    encode_2d(fn, &mH, hptr, kHP, kM, 64, 128);
    encode_2d(fn, &mHq, hptr, kHP, kM, 64, 64);
    encode_2d(fn, &mW2h, d_in[3], kD, kF, 64, 32);
    cudaFuncSetAttribute(ffn_fused_kernel, cudaFuncAttributeMaxDynamicSharedMemorySize, kSmemBytes);
    cached[0] = d_in[0]; cached[1] = d_in[1]; cached[2] = d_in[3];
    init = true;
  }
  ffn_fused_kernel<<<128, kThreads, kSmemBytes, cudaStreamPerThread>>>(
      (const __nv_bfloat16*)d_in[2], (const __nv_bfloat16*)d_in[4], (__nv_bfloat16*)d_out, (const uint8_t*)d_in[1],
      (const uint8_t*)d_in[3], mX, mW1, mW1h, mH, mHq, mW2h);
}
```

```cpp
#include <cuda_runtime.h>
#include <cuda_bf16.h>
#include <cuda.h>
#include <stdint.h>

namespace {

constexpr int kM = 2048, kD = 512, kF = 1376;
constexpr int kHP = 1408;
constexpr int kThreads = 384;
constexpr uint32_t kASlot = 16384;
constexpr uint32_t kBSlot = 8192;
constexpr uint32_t kOffA = 0, kOffB = 8 * kASlot, kOffStage = kOffB + 8 * kBSlot, kOffBar = kOffStage + 2 * kASlot;
constexpr uint32_t kSmemBytes = kOffBar + 1024 + 1024;
constexpr uint32_t kMbarSpins = 1u << 18, kFlagSpins = 1u << 20;

__device__ __align__(1024) __nv_bfloat16 g_h[kM * kHP];
__device__ unsigned g_flags[16 * 3 * 8];
__device__ unsigned g_done;

__device__ __forceinline__ uint32_t smem_u32(const void* p) { return (uint32_t)__cvta_generic_to_shared(p); }
__device__ __forceinline__ void mbar_init(uint32_t bar, uint32_t cnt) {
  asm volatile("mbarrier.init.shared::cta.b64 [%0], %1;" ::"r"(bar), "r"(cnt) : "memory");
}
__device__ __forceinline__ void mbar_expect_tx(uint32_t bar, uint32_t bytes) {
  asm volatile("mbarrier.arrive.expect_tx.shared::cta.b64 _, [%0], %1;" ::"r"(bar), "r"(bytes) : "memory");
}
__device__ __forceinline__ void mbar_arrive(uint32_t bar) {
  asm volatile("mbarrier.arrive.shared::cta.b64 _, [%0];" ::"r"(bar) : "memory");
}
__device__ __forceinline__ void mbar_arrive_remote(uint32_t cluster_addr) {
  asm volatile("mbarrier.arrive.shared::cluster.b64 _, [%0];" ::"r"(cluster_addr) : "memory");
}
__device__ __forceinline__ void mbar_wait(uint32_t bar, uint32_t parity) {
  uint32_t ok;
#pragma unroll 1
  for (uint32_t i = 0; i < kMbarSpins; i++) {
    asm volatile("{\n.reg .pred p;\nmbarrier.try_wait.parity.shared::cta.b64 p, [%1], %2;\nselp.u32 %0, 1, 0, p;\n}"
                 : "=r"(ok) : "r"(bar), "r"(parity) : "memory");
    if (ok) return;
  }
  __trap();
}
__device__ __forceinline__ bool mbar_test(uint32_t bar, uint32_t parity) {
  uint32_t ok;
  asm volatile("{\n.reg .pred p;\nmbarrier.test_wait.parity.shared::cta.b64 p, [%1], %2;\nselp.u32 %0, 1, 0, p;\n}"
               : "=r"(ok) : "r"(bar), "r"(parity) : "memory");
  return ok;
}
__device__ __forceinline__ bool elect_one() {
  uint32_t pred;
  asm volatile("{\n.reg .pred p;\nelect.sync _|p, 0xffffffff;\nselp.u32 %0, 1, 0, p;\n}" : "=r"(pred));
  return pred;
}
__device__ __forceinline__ void tma_load(uint32_t dst, const CUtensorMap* map, uint32_t bar, int c0, int c1) {
  asm volatile("cp.async.bulk.tensor.2d.shared::cluster.global.mbarrier::complete_tx::bytes [%0], [%1, {%3, %4}], [%2];"
               ::"r"(dst), "l"(map), "r"(bar), "r"(c0), "r"(c1) : "memory");
}
__device__ __forceinline__ void tma_load_pair(uint32_t dst, const CUtensorMap* map, uint32_t bar, int c0, int c1) {
  asm volatile("cp.async.bulk.tensor.2d.shared::cluster.global.mbarrier::complete_tx::bytes.multicast::cluster [%0], [%1, {%3, %4}], [%2], %5;"
               ::"r"(dst), "l"(map), "r"(bar), "r"(c0), "r"(c1), "h"((uint16_t)3) : "memory");
}
__device__ __forceinline__ void tma_store(const CUtensorMap* map, uint32_t src, int c0, int c1) {
  asm volatile("cp.async.bulk.tensor.2d.global.shared::cta.bulk_group [%0, {%2, %3}], [%1];"
               ::"l"(map), "r"(src), "r"(c0), "r"(c1) : "memory");
}
__device__ __forceinline__ void cluster_arrive() { asm volatile("barrier.cluster.arrive.relaxed.aligned;" ::: "memory"); }
__device__ __forceinline__ void cluster_wait() { asm volatile("barrier.cluster.wait.aligned;" ::: "memory"); }
__device__ __forceinline__ void bar_sync(int id, int n) { asm volatile("bar.sync %0, %1;" ::"r"(id), "r"(n) : "memory"); }
__device__ __forceinline__ void bar_arrive(int id, int n) { asm volatile("bar.arrive %0, %1;" ::"r"(id), "r"(n) : "memory"); }
__device__ __forceinline__ void fence_async_smem() { asm volatile("fence.proxy.async.shared::cta;" ::: "memory"); }
__device__ __forceinline__ void wg_fence() { asm volatile("wgmma.fence.sync.aligned;" ::: "memory"); }
__device__ __forceinline__ void wg_commit() { asm volatile("wgmma.commit_group.sync.aligned;" ::: "memory"); }
template <int N> __device__ __forceinline__ void wg_wait() { asm volatile("wgmma.wait_group.sync.aligned %0;" ::"n"(N) : "memory"); }
__device__ __forceinline__ void fence_acc(float (&d)[64]) {
#pragma unroll
  for (int i = 0; i < 64; i++) asm volatile("" : "+f"(d[i])::"memory");
}
__device__ __forceinline__ uint64_t make_desc(uint32_t addr) {
  return (uint64_t)((addr & 0x3FFFF) >> 4) | ((uint64_t)1 << 16) | ((uint64_t)(1024 >> 4) << 32) | ((uint64_t)1 << 62);
}

__device__ __forceinline__ void wgmma_t128(float (&d)[64], uint64_t da, uint64_t db, uint32_t scale_d) {
  asm volatile("{\n.reg .pred p;\nsetp.ne.b32 p, %66, 0;\n"
      "wgmma.mma_async.sync.aligned.m64n128k16.f32.bf16.bf16 "
      "{%0, %1, %2, %3, %4, %5, %6, %7, %8, %9, %10, %11, %12, %13, %14, %15, "
      "%16, %17, %18, %19, %20, %21, %22, %23, %24, %25, %26, %27, %28, %29, %30, %31, "
      "%32, %33, %34, %35, %36, %37, %38, %39, %40, %41, %42, %43, %44, %45, %46, %47, "
      "%48, %49, %50, %51, %52, %53, %54, %55, %56, %57, %58, %59, %60, %61, %62, %63}, "
      "%64, %65, p, 1, 1, 1, 0;\n}\n"
    : "+f"(d[0]), "+f"(d[1]), "+f"(d[2]), "+f"(d[3]), "+f"(d[4]), "+f"(d[5]), "+f"(d[6]), "+f"(d[7]),
      "+f"(d[8]), "+f"(d[9]), "+f"(d[10]), "+f"(d[11]), "+f"(d[12]), "+f"(d[13]), "+f"(d[14]), "+f"(d[15]),
      "+f"(d[16]), "+f"(d[17]), "+f"(d[18]), "+f"(d[19]), "+f"(d[20]), "+f"(d[21]), "+f"(d[22]), "+f"(d[23]),
      "+f"(d[24]), "+f"(d[25]), "+f"(d[26]), "+f"(d[27]), "+f"(d[28]), "+f"(d[29]), "+f"(d[30]), "+f"(d[31]),
      "+f"(d[32]), "+f"(d[33]), "+f"(d[34]), "+f"(d[35]), "+f"(d[36]), "+f"(d[37]), "+f"(d[38]), "+f"(d[39]),
      "+f"(d[40]), "+f"(d[41]), "+f"(d[42]), "+f"(d[43]), "+f"(d[44]), "+f"(d[45]), "+f"(d[46]), "+f"(d[47]),
      "+f"(d[48]), "+f"(d[49]), "+f"(d[50]), "+f"(d[51]), "+f"(d[52]), "+f"(d[53]), "+f"(d[54]), "+f"(d[55]),
      "+f"(d[56]), "+f"(d[57]), "+f"(d[58]), "+f"(d[59]), "+f"(d[60]), "+f"(d[61]), "+f"(d[62]), "+f"(d[63])
    : "l"(da), "l"(db), "r"(scale_d));
}

__device__ __forceinline__ uint32_t pack_bf16(float lo, float hi) {
  uint32_t r;
  asm("cvt.rn.bf16x2.f32 %0, %1, %2;" : "=r"(r) : "f"(hi), "f"(lo));
  return r;
}
__device__ __forceinline__ void stmatrix_x4_trans(uint32_t addr, uint32_t r0, uint32_t r1, uint32_t r2, uint32_t r3) {
  asm volatile("stmatrix.sync.aligned.m8n8.x4.trans.shared.b16 [%0], {%1, %2, %3, %4};" ::"r"(addr), "r"(r0), "r"(r1), "r"(r2), "r"(r3) : "memory");
}
__device__ __forceinline__ uint4 lds128(uint32_t addr) {
  uint4 v;
  asm volatile("ld.shared.v4.b32 {%0, %1, %2, %3}, [%4];" : "=r"(v.x), "=r"(v.y), "=r"(v.z), "=r"(v.w) : "r"(addr) : "memory");
  return v;
}
__device__ __forceinline__ float lds_bf16(uint32_t addr) {
  uint32_t v;
  asm volatile("ld.shared.u16 %0, [%1];" : "=r"(v) : "r"(addr) : "memory");
  return __uint_as_float(v << 16);
}
__device__ __forceinline__ unsigned ld_flag(const unsigned* f) {
  unsigned v;
  asm volatile("ld.relaxed.gpu.global.u32 %0, [%1];" : "=r"(v) : "l"(f) : "memory");
  return v;
}
__device__ __forceinline__ float gelu2(float v, float k1) {
  const float p = fmaf(v * v, k1, 0.7978845608028654f);
  float t;
  asm("tanh.approx.f32 %0, %1;" : "=f"(t) : "f"(v * p));
  return fmaf(v, t, v);
}

__device__ __forceinline__ int unit_of(int j, int t) { return j < 6 ? 3 * j + t : (t < 2 ? 2 * j + 6 + t : 22); }

__device__ __forceinline__ void release_slot(uint32_t bar, uint32_t peer_bar, int s, bool pred, bool pred_a) {
  if (pred_a) mbar_arrive(bar + 256 + s * 8);
  if (pred) { mbar_arrive(bar + 64 + s * 8); mbar_arrive_remote(peer_bar + 64 + s * 8); }
}
__device__ __forceinline__ void mma_round(float (&acc)[64], uint64_t dw, uint64_t dx, uint32_t bar, uint32_t peer_bar, uint32_t parity,
                                          uint32_t& ok, int nblk, uint32_t accumulate, bool rel_lo, bool rel_hi, bool rel_a,
                                          bool short_last, int next_bar) {
#pragma unroll
  for (int s = 0; s < 8; s++) {
    if (s >= 6 && s >= nblk) break;
    if (!ok) mbar_wait(bar + s * 8, parity);
    const uint64_t w = dw + s * (kBSlot >> 4), x = dx + s * (kASlot >> 4);
    if (s == 7 && short_last) {
      wg_fence();
      wgmma_t128(acc, w, x, 1u);
      wgmma_t128(acc, w + 128, x + 2, 1u);
      wg_commit();
    } else {
      wg_fence();
      wgmma_t128(acc, w, x, s == 0 ? accumulate : 1u);
      wgmma_t128(acc, w + 128, x + 2, 1u);
      wgmma_t128(acc, w + 256, x + 4, 1u);
      wgmma_t128(acc, w + 384, x + 6, 1u);
      wg_commit();
    }
    if (s == 7 && next_bar) bar_arrive(next_bar, 256);
    const bool rel = s < 2 ? rel_lo : rel_hi;
    release_slot(bar, peer_bar, (s + 6) & 7, rel, rel && rel_a);
    ok = mbar_test(bar + ((s + 1) & 7) * 8, s == 7 ? parity ^ 1u : parity);
    wg_wait<1>();
  }
}

__device__ __forceinline__ uint32_t stage_addr(uint32_t tile, int w, int lane) {
  const int m = lane >> 3, r7 = lane & 7;
  return tile + ((m >> 1) * 8 + r7) * 128 + (((2 * w + (m & 1)) ^ r7) << 4);
}

__global__ void __cluster_dims__(2, 1, 1) __launch_bounds__(kThreads, 1)
ffn_fused_kernel(const __nv_bfloat16* __restrict__ b1, const __nv_bfloat16* __restrict__ b2, __nv_bfloat16* __restrict__ out,
                 const __grid_constant__ CUtensorMap mX, const __grid_constant__ CUtensorMap mW1,
                 const __grid_constant__ CUtensorMap mW1h, const __grid_constant__ CUtensorMap mH,
                 const __grid_constant__ CUtensorMap mHs, const __grid_constant__ CUtensorMap mW2h) {
  extern __shared__ uint8_t smem_raw[];
  uint32_t base = (smem_u32(smem_raw) + 1023u) & ~1023u;
  asm volatile("mov.u32 %0, %0;" : "+r"(base));
  const uint32_t sA = base + kOffA, sB = base + kOffB, sStage = base + kOffStage;
  const uint32_t bar_full = base + kOffBar;
  const uint32_t bar_empty = bar_full + 64;
  const uint32_t bar_staged = bar_full + 128;
  const uint32_t bar_stfree = bar_full + 224;
  const uint32_t bar_bias = bar_full + 232;
  const uint32_t bar_emptyA = bar_full + 256;
  const uint32_t sBias = bar_full + 320;
  const uint32_t bar_hf = bar_full + 832;
  const int warp = __shfl_sync(0xffffffff, threadIdx.x >> 5, 0);
  const int lane = threadIdx.x & 31;

  int grp, j;
  {
    const int c = blockIdx.x >> 1;
    int gpc;
    if (c < 4) { gpc = 0; j = 4 + c; }
    else if (c < 36) { gpc = (c - 4) & 7; j = (c - 4) >> 3; }
    else { gpc = 1 + (c - 36) % 7; j = 4 + (c - 36) / 7; }
    grp = 2 * gpc + (blockIdx.x & 1);
  }
  const int row0 = grp * 128;
  const uint32_t rank = blockIdx.x & 1;

  constexpr int kEarly = 2;
  {
    uint32_t tid_opaque = threadIdx.x;
    asm volatile("" : "+r"(tid_opaque));
    if (__builtin_expect(tid_opaque == 256, 1)) {
#pragma unroll
      for (int i = 0; i < 8; i++) mbar_init(bar_full + i * 8, 1);
      asm volatile("fence.mbarrier_init.release.cluster;" ::: "memory");
#pragma unroll
      for (int kb = 0; kb < kEarly; kb++) {
        mbar_expect_tx(bar_full + kb * 8, kASlot + kBSlot);
        tma_load(sA + kb * kASlot, &mX, bar_full + kb * 8, kb * 64, row0);
        tma_load(sB + kb * kBSlot, &mW1, bar_full + kb * 8, 64 * unit_of(j, 0), kb * 64);
      }
    }
    __syncwarp();
  }

  if (warp == 8) {
    bar_arrive(1, kThreads - 32);
    cluster_arrive();
    if (elect_one()) {
#pragma unroll
      for (int kb = kEarly; kb < 8; kb++) {
        mbar_expect_tx(bar_full + kb * 8, kASlot + kBSlot);
        tma_load(sA + kb * kASlot, &mX, bar_full + kb * 8, kb * 64, row0);
        tma_load(sB + kb * kBSlot, &mW1, bar_full + kb * 8, 64 * unit_of(j, 0), kb * 64);
      }
    }
    __syncwarp();
    cluster_wait();
#pragma unroll 1
    for (int it = 8; it < 24; it++) {
      const int s = it & 7, t = it >> 3;
      mbar_wait(bar_empty + s * 8, (t - 1) & 1);
      if (elect_one()) {
        mbar_expect_tx(bar_full + s * 8, kBSlot);
        tma_load_pair(sB + s * kBSlot + rank * 4096, &mW1h, bar_full + s * 8, 64 * unit_of(j, t), s * 64 + rank * 32);
      }
      __syncwarp();
    }
#pragma unroll 1
    for (int q = 0; q < 22; q++) {
      const uint32_t off = (q & 7) * 8;
      mbar_wait(bar_empty + off, (q >> 3) & 1);
      if (elect_one()) {
        mbar_expect_tx(bar_full + off, kASlot + kBSlot);
        tma_load_pair(sB + off * (kBSlot / 8) + rank * 4096, &mW2h, bar_full + off, j * 64, 64 * unit_of(q & 7, q >> 3) + rank * 32);
      }
      __syncwarp();
    }
  } else if (warp == 9) {
    if (elect_one()) {
#pragma unroll
      for (int i = 0; i < 8; i++) mbar_init(bar_empty + i * 8, 8);
      mbar_init(bar_bias, 1);
#pragma unroll
      for (int i = 0; i < 6; i++) mbar_init(bar_staged + i * 8, 4);
      mbar_init(bar_stfree, 1);
#pragma unroll
      for (int i = 0; i < 8; i++) mbar_init(bar_emptyA + i * 8, 4);
#pragma unroll
      for (int i = 0; i < 24; i++) mbar_init(bar_hf + i * 8, 1);
      asm volatile("fence.mbarrier_init.release.cluster;" ::: "memory");
    }
    __syncwarp();
    bar_arrive(6, 64);
    cluster_arrive();
    bar_sync(1, kThreads - 32);
    cluster_wait();
#pragma unroll 1
    for (int q = 0; q < 22; q++) {
      const uint32_t off = (q & 7) * 8, par = (q >> 3) & 1;
      const bool published = mbar_test(bar_hf + q * 8, 0), vacant = mbar_test(bar_emptyA + off, par);
      if (!published) mbar_wait(bar_hf + q * 8, 0);
      if (off == 0) asm volatile("fence.proxy.async.global;" ::: "memory");
      if (!vacant) mbar_wait(bar_emptyA + off, par);
      if (elect_one()) tma_load(sA + off * (kASlot / 8), &mH, bar_full + off, 64 * unit_of(q & 7, q >> 3), row0);
      __syncwarp();
    }
  } else if (warp == 11) {
    cluster_arrive();
    bar_sync(1, kThreads - 32);
    cluster_wait();
    const unsigned target = (ld_flag(&g_done) >> 7) + 1u;
#pragma unroll 1
    for (int t = 0; t < 3; t++) {
      const uint32_t want = t < 2 ? 0xffu : 0x3fu;
      const unsigned* f = &g_flags[(grp * 3 + t) * 8 + (lane & 7)];
      uint32_t seen = 0;
      unsigned v0 = ld_flag(f);
      __nanosleep(60);
      unsigned v1 = ld_flag(f);
#pragma unroll 1
      for (uint32_t spins = 0;; spins++) {
        uint32_t m = __ballot_sync(0xffffffff, (int)(v0 - target) >= 0) & want;
        if (lane < 8 && (((m & ~seen) >> lane) & 1u)) mbar_arrive(bar_hf + (t * 8 + lane) * 8);
        seen |= m;
        if (seen == want) break;
        v0 = ld_flag(f);
        m = __ballot_sync(0xffffffff, (int)(v1 - target) >= 0) & want;
        if (lane < 8 && (((m & ~seen) >> lane) & 1u)) mbar_arrive(bar_hf + (t * 8 + lane) * 8);
        seen |= m;
        if (seen == want) break;
        v1 = ld_flag(f);
        if (spins > kFlagSpins) __trap();
      }
    }
  } else if (warp == 10) {
    cluster_arrive();
    {
      uint32_t v[4];
#pragma unroll
      for (int i = 0; i < 3; i++) {
        const int c = 64 * unit_of(j, i) + 2 * lane;
        v[i] = c < kF ? __ldg(reinterpret_cast<const uint32_t*>(b1 + c)) : 0u;
      }
      v[3] = __ldg(reinterpret_cast<const uint32_t*>(b2 + j * 64 + 2 * lane));
#pragma unroll
      for (int i = 0; i < 4; i++) asm volatile("st.shared.u32 [%0], %1;" ::"r"(sBias + i * 128 + lane * 4), "r"(v[i]) : "memory");
      bar_sync(6, 64);
      if (lane == 0) mbar_arrive(bar_bias);
    }
    cluster_wait();
    const int nt = j < 6 ? 3 : 2;
#pragma unroll 1
    for (int t = 0; t < nt; t++) {
#pragma unroll 1
      for (int hf = 0; hf < 2; hf++) {
        mbar_wait(bar_staged + (t * 2 + hf) * 8, 0);
        if (elect_one()) {
          tma_store(&mHs, sStage + (t & 1) * kASlot + hf * 8192, 64 * unit_of(j, t), row0 + hf * 64);
          asm volatile("cp.async.bulk.commit_group;" ::: "memory");
        }
        __syncwarp();
      }
      if (elect_one()) {
        asm volatile("cp.async.bulk.wait_group 0;" ::: "memory");
        asm volatile("red.relaxed.gpu.global.add.u32 [%0], 1;" ::"l"(&g_flags[(grp * 3 + t) * 8 + j]) : "memory");
        if (t == 0) mbar_arrive(bar_stfree);
      }
      __syncwarp();
    }
  } else {
    const int wg = warp >> 2, w = warp & 3;
    const int my_turn = wg ? 2 : 3, other_turn = wg ? 3 : 2;
    const bool leader = lane == 0;
    float acc[64];
    const uint64_t dx0 = make_desc(sA), dw0 = make_desc(sB);
    const int mcol = 16 * w + (lane >> 2);
    uint32_t peer_bar;
    asm volatile("mapa.shared::cluster.u32 %0, %1, %2;" : "=r"(peer_bar) : "r"(bar_full), "r"(rank ^ 1));
    cluster_arrive();
    bar_sync(1, kThreads - 32);
    cluster_wait();
    const uint32_t zero = blockIdx.y;
#pragma unroll 1
    for (int round = wg; round < 4; round += 2) {
      uint32_t accumulate = 0u;
      if (round < 3) {
        mbar_wait(bar_bias, 0);
        const float c0 = lds_bf16(sBias + round * 128 + mcol * 2), c1 = lds_bf16(sBias + round * 128 + mcol * 2 + 16);
#pragma unroll
        for (int g = 0; g < 16; g++) { acc[4 * g] = c0; acc[4 * g + 1] = c0; acc[4 * g + 2] = c1; acc[4 * g + 3] = c1; }
        accumulate = 1u;
      }
      fence_acc(acc);
      if (round > 0) bar_sync(my_turn, 256);
      uint32_t ok = 0;
      const int last = round == 3 ? 5 : round;
#pragma unroll 1
      for (int rr = round; rr <= last; rr++) {
        mma_round(acc, dw0, dx0, bar_full, peer_bar, rr & 1, ok, rr == 5 ? 6 : 8, accumulate, leader && rr == 4, leader && rr != 5,
                  rr >= 2, rr == 4, rr < 3 ? other_turn : 0);
        accumulate = 1u;
      }
      if (round < 3) release_slot(bar_full, peer_bar, 6, leader, leader && round == 2);
      wg_wait<0>();
      fence_acc(acc);
      if (round == 3) break;
      release_slot(bar_full, peer_bar, 7, leader, leader && round == 2);
      if (round == 2) mbar_wait(bar_stfree, 0);
      const uint32_t sa = stage_addr(sStage + wg * kASlot, w, lane);
      uint32_t dep = 0;
#pragma unroll
      for (int gp = 0; gp < 8; gp++) {
        const float k1 = __uint_as_float(__float_as_uint(0.035677408136300125f) | (dep & zero));
        uint32_t p[4];
#pragma unroll
        for (int h = 0; h < 2; h++) {
          const int g = 2 * gp + h;
          p[2 * h] = pack_bf16(gelu2(acc[4 * g], k1), gelu2(acc[4 * g + 1], k1));
          p[2 * h + 1] = pack_bf16(gelu2(acc[4 * g + 2], k1), gelu2(acc[4 * g + 3], k1));
        }
        dep = p[3];
        if (gp == 4) {
          fence_async_smem();
          __syncwarp();
          if (leader) mbar_arrive(bar_staged + round * 16);
        }
        stmatrix_x4_trans(sa + gp * 2048, p[0], p[1], p[2], p[3]);
        __syncwarp();
      }
      fence_async_smem();
      __syncwarp();
      if (leader) mbar_arrive(bar_staged + round * 16 + 8);
    }
    if (wg == 1) {
      const float bias0 = lds_bf16(sBias + 384 + mcol * 2), bias1 = lds_bf16(sBias + 384 + mcol * 2 + 16);
      const uint32_t otile = sA + 7 * kASlot;
      const uint32_t sa = stage_addr(otile, w, lane);
#pragma unroll
      for (int gp = 0; gp < 8; gp++) {
        uint32_t p[4];
#pragma unroll
        for (int h = 0; h < 2; h++) {
          const int g = 2 * gp + h;
          p[2 * h] = pack_bf16(fmaf(acc[4 * g], 0.5f, bias0), fmaf(acc[4 * g + 1], 0.5f, bias0));
          p[2 * h + 1] = pack_bf16(fmaf(acc[4 * g + 2], 0.5f, bias1), fmaf(acc[4 * g + 3], 0.5f, bias1));
        }
        stmatrix_x4_trans(sa + gp * 2048, p[0], p[1], p[2], p[3]);
      }
      bar_sync(4, 128);
      const int t = threadIdx.x & 127, ch = t & 7;
      __nv_bfloat16* optr = out + (size_t)(row0 + (t >> 3)) * kD + j * 64 + ch * 8;
#pragma unroll
      for (int i = 0; i < 8; i++) {
        const int row = 16 * i + (t >> 3);
        const uint4 v = lds128(otile + row * 128 + ((ch ^ (row & 7)) << 4));
        *reinterpret_cast<uint4*>(optr + (size_t)i * 16 * kD) = v;
      }
      if (t == 0) asm volatile("red.relaxed.gpu.global.add.u32 [%0], 1;" ::"l"(&g_done) : "memory");
    }
  }
}

typedef CUresult (*EncodeTiledFn)(CUtensorMap*, CUtensorMapDataType, cuuint32_t, void*, const cuuint64_t*, const cuuint64_t*,
                                  const cuuint32_t*, const cuuint32_t*, CUtensorMapInterleave, CUtensorMapSwizzle,
                                  CUtensorMapL2promotion, CUtensorMapFloatOOBfill);

void encode_2d(EncodeTiledFn fn, CUtensorMap* m, const void* ptr, uint64_t cols, uint64_t rows, uint32_t box_cols, uint32_t box_rows) {
  cuuint64_t dims[2] = {cols, rows};
  cuuint64_t strides[1] = {cols * 2};
  cuuint32_t box[2] = {box_cols, box_rows};
  cuuint32_t es[2] = {1, 1};
  fn(m, CU_TENSOR_MAP_DATA_TYPE_BFLOAT16, 2, const_cast<void*>(ptr), dims, strides, box, es, CU_TENSOR_MAP_INTERLEAVE_NONE,
     CU_TENSOR_MAP_SWIZZLE_128B, CU_TENSOR_MAP_L2_PROMOTION_L2_128B, CU_TENSOR_MAP_FLOAT_OOB_FILL_NONE);
}

}

extern "C" void kernel_launch(void* const* d_in, const int* in_sizes, int n_in, void* d_out, int out_size) {
  (void)in_sizes; (void)n_in; (void)out_size;
  static CUtensorMap mX, mW1, mW1h, mH, mHs, mW2h;
  static const void* cached[3] = {nullptr, nullptr, nullptr};
  if (cached[0] != d_in[0] || cached[1] != d_in[1] || cached[2] != d_in[3]) {
    void* fnp = nullptr;
    cudaDriverEntryPointQueryResult st;
    cudaGetDriverEntryPoint("cuTensorMapEncodeTiled", &fnp, cudaEnableDefault, &st);
    EncodeTiledFn fn = (EncodeTiledFn)fnp;
    void* hptr = nullptr;
    cudaGetSymbolAddress(&hptr, g_h);
    encode_2d(fn, &mX, d_in[0], kD, kM, 64, 128);
    encode_2d(fn, &mW1, d_in[1], kF, kD, 64, 64);
    encode_2d(fn, &mW1h, d_in[1], kF, kD, 64, 32);
    encode_2d(fn, &mH, hptr, kHP, kM, 64, 128);
    encode_2d(fn, &mHs, hptr, kHP, kM, 64, 64);
    encode_2d(fn, &mW2h, d_in[3], kD, kF, 64, 32);
    cudaFuncSetAttribute(ffn_fused_kernel, cudaFuncAttributeMaxDynamicSharedMemorySize, kSmemBytes);
    cached[0] = d_in[0]; cached[1] = d_in[1]; cached[2] = d_in[3];
  }
  ffn_fused_kernel<<<128, kThreads, kSmemBytes, cudaStreamPerThread>>>(
      (const __nv_bfloat16*)d_in[2], (const __nv_bfloat16*)d_in[4], (__nv_bfloat16*)d_out, mX, mW1, mW1h, mH, mHs, mW2h);
}
```

```cpp
#include <cuda_runtime.h>
#include <cuda_bf16.h>
#include <cuda.h>
#include <stdint.h>

namespace {

constexpr int kM = 2048, kD = 512, kF = 1376;
constexpr int kHP = 1408;
constexpr int kThreads = 384;
constexpr uint32_t kASlot = 16384;
constexpr uint32_t kBSlot = 8192;
constexpr uint32_t kOffA = 0, kOffB = 8 * kASlot, kOffStage = kOffB + 8 * kBSlot, kOffBar = kOffStage + 2 * kASlot;
constexpr uint32_t kSmemBytes = kOffBar + 1024 + 1024;
constexpr uint32_t kMbarSpins = 1u << 18, kFlagSpins = 1u << 20;

__device__ __align__(1024) __nv_bfloat16 g_h[kM * kHP];
__device__ unsigned g_flags[16 * 3 * 8];
__device__ unsigned g_done;

__device__ __forceinline__ uint32_t smem_u32(const void* p) { return (uint32_t)__cvta_generic_to_shared(p); }
__device__ __forceinline__ void mbar_init(uint32_t bar, uint32_t cnt) {
  asm volatile("mbarrier.init.shared::cta.b64 [%0], %1;" ::"r"(bar), "r"(cnt) : "memory");
}
__device__ __forceinline__ void mbar_expect_tx(uint32_t bar, uint32_t bytes) {
  asm volatile("mbarrier.arrive.expect_tx.shared::cta.b64 _, [%0], %1;" ::"r"(bar), "r"(bytes) : "memory");
}
__device__ __forceinline__ void mbar_arrive(uint32_t bar) {
  asm volatile("mbarrier.arrive.shared::cta.b64 _, [%0];" ::"r"(bar) : "memory");
}
__device__ __forceinline__ void mbar_arrive_remote(uint32_t cluster_addr) {
  asm volatile("mbarrier.arrive.shared::cluster.b64 _, [%0];" ::"r"(cluster_addr) : "memory");
}
__device__ __forceinline__ void mbar_wait(uint32_t bar, uint32_t parity) {
  uint32_t ok;
#pragma unroll 1
  for (uint32_t i = 0; i < kMbarSpins; i++) {
    asm volatile("{\n.reg .pred p;\nmbarrier.try_wait.parity.shared::cta.b64 p, [%1], %2;\nselp.u32 %0, 1, 0, p;\n}"
                 : "=r"(ok) : "r"(bar), "r"(parity) : "memory");
    if (ok) return;
  }
  __trap();
}
__device__ __forceinline__ bool mbar_test(uint32_t bar, uint32_t parity) {
  uint32_t ok;
  asm volatile("{\n.reg .pred p;\nmbarrier.test_wait.parity.shared::cta.b64 p, [%1], %2;\nselp.u32 %0, 1, 0, p;\n}"
               : "=r"(ok) : "r"(bar), "r"(parity) : "memory");
  return ok;
}
__device__ __forceinline__ bool elect_one() {
  uint32_t pred;
  asm volatile("{\n.reg .pred p;\nelect.sync _|p, 0xffffffff;\nselp.u32 %0, 1, 0, p;\n}" : "=r"(pred));
  return pred;
}
__device__ __forceinline__ void tma_load(uint32_t dst, const CUtensorMap* map, uint32_t bar, int c0, int c1) {
  asm volatile("cp.async.bulk.tensor.2d.shared::cluster.global.mbarrier::complete_tx::bytes [%0], [%1, {%3, %4}], [%2];"
               ::"r"(dst), "l"(map), "r"(bar), "r"(c0), "r"(c1) : "memory");
}
__device__ __forceinline__ void tma_load_pair(uint32_t dst, const CUtensorMap* map, uint32_t bar, int c0, int c1) {
  asm volatile("cp.async.bulk.tensor.2d.shared::cluster.global.mbarrier::complete_tx::bytes.multicast::cluster [%0], [%1, {%3, %4}], [%2], %5;"
               ::"r"(dst), "l"(map), "r"(bar), "r"(c0), "r"(c1), "h"((uint16_t)3) : "memory");
}
__device__ __forceinline__ void tma_store(const CUtensorMap* map, uint32_t src, int c0, int c1) {
  asm volatile("cp.async.bulk.tensor.2d.global.shared::cta.bulk_group [%0, {%2, %3}], [%1];"
               ::"l"(map), "r"(src), "r"(c0), "r"(c1) : "memory");
}
__device__ __forceinline__ void cluster_arrive() { asm volatile("barrier.cluster.arrive.relaxed.aligned;" ::: "memory"); }
__device__ __forceinline__ void cluster_wait() { asm volatile("barrier.cluster.wait.aligned;" ::: "memory"); }
__device__ __forceinline__ void bar_sync(int id, int n) { asm volatile("bar.sync %0, %1;" ::"r"(id), "r"(n) : "memory"); }
__device__ __forceinline__ void bar_arrive(int id, int n) { asm volatile("bar.arrive %0, %1;" ::"r"(id), "r"(n) : "memory"); }
__device__ __forceinline__ void fence_async_smem() { asm volatile("fence.proxy.async.shared::cta;" ::: "memory"); }
__device__ __forceinline__ void wg_fence() { asm volatile("wgmma.fence.sync.aligned;" ::: "memory"); }
__device__ __forceinline__ void wg_commit() { asm volatile("wgmma.commit_group.sync.aligned;" ::: "memory"); }
template <int N> __device__ __forceinline__ void wg_wait() { asm volatile("wgmma.wait_group.sync.aligned %0;" ::"n"(N) : "memory"); }
__device__ __forceinline__ void fence_acc(float (&d)[64]) {
#pragma unroll
  for (int i = 0; i < 64; i++) asm volatile("" : "+f"(d[i])::"memory");
}
__device__ __forceinline__ uint64_t make_desc(uint32_t addr) {
  return (uint64_t)((addr & 0x3FFFF) >> 4) | ((uint64_t)1 << 16) | ((uint64_t)(1024 >> 4) << 32) | ((uint64_t)1 << 62);
}

__device__ __forceinline__ void wgmma_t128(float (&d)[64], uint64_t da, uint64_t db, uint32_t scale_d) {
  asm volatile("{\n.reg .pred p;\nsetp.ne.b32 p, %66, 0;\n"
      "wgmma.mma_async.sync.aligned.m64n128k16.f32.bf16.bf16 "
      "{%0, %1, %2, %3, %4, %5, %6, %7, %8, %9, %10, %11, %12, %13, %14, %15, "
      "%16, %17, %18, %19, %20, %21, %22, %23, %24, %25, %26, %27, %28, %29, %30, %31, "
      "%32, %33, %34, %35, %36, %37, %38, %39, %40, %41, %42, %43, %44, %45, %46, %47, "
      "%48, %49, %50, %51, %52, %53, %54, %55, %56, %57, %58, %59, %60, %61, %62, %63}, "
      "%64, %65, p, 1, 1, 1, 0;\n}\n"
    : "+f"(d[0]), "+f"(d[1]), "+f"(d[2]), "+f"(d[3]), "+f"(d[4]), "+f"(d[5]), "+f"(d[6]), "+f"(d[7]),
      "+f"(d[8]), "+f"(d[9]), "+f"(d[10]), "+f"(d[11]), "+f"(d[12]), "+f"(d[13]), "+f"(d[14]), "+f"(d[15]),
      "+f"(d[16]), "+f"(d[17]), "+f"(d[18]), "+f"(d[19]), "+f"(d[20]), "+f"(d[21]), "+f"(d[22]), "+f"(d[23]),
      "+f"(d[24]), "+f"(d[25]), "+f"(d[26]), "+f"(d[27]), "+f"(d[28]), "+f"(d[29]), "+f"(d[30]), "+f"(d[31]),
      "+f"(d[32]), "+f"(d[33]), "+f"(d[34]), "+f"(d[35]), "+f"(d[36]), "+f"(d[37]), "+f"(d[38]), "+f"(d[39]),
      "+f"(d[40]), "+f"(d[41]), "+f"(d[42]), "+f"(d[43]), "+f"(d[44]), "+f"(d[45]), "+f"(d[46]), "+f"(d[47]),
      "+f"(d[48]), "+f"(d[49]), "+f"(d[50]), "+f"(d[51]), "+f"(d[52]), "+f"(d[53]), "+f"(d[54]), "+f"(d[55]),
      "+f"(d[56]), "+f"(d[57]), "+f"(d[58]), "+f"(d[59]), "+f"(d[60]), "+f"(d[61]), "+f"(d[62]), "+f"(d[63])
    : "l"(da), "l"(db), "r"(scale_d));
}

__device__ __forceinline__ uint32_t pack_bf16(float lo, float hi) {
  uint32_t r;
  asm("cvt.rn.bf16x2.f32 %0, %1, %2;" : "=r"(r) : "f"(hi), "f"(lo));
  return r;
}
__device__ __forceinline__ void stmatrix_x4_trans(uint32_t addr, uint32_t r0, uint32_t r1, uint32_t r2, uint32_t r3) {
  asm volatile("stmatrix.sync.aligned.m8n8.x4.trans.shared.b16 [%0], {%1, %2, %3, %4};" ::"r"(addr), "r"(r0), "r"(r1), "r"(r2), "r"(r3) : "memory");
}
__device__ __forceinline__ uint4 lds128(uint32_t addr) {
  uint4 v;
  asm volatile("ld.shared.v4.b32 {%0, %1, %2, %3}, [%4];" : "=r"(v.x), "=r"(v.y), "=r"(v.z), "=r"(v.w) : "r"(addr) : "memory");
  return v;
}
__device__ __forceinline__ float lds_bf16(uint32_t addr) {
  uint32_t v;
  asm volatile("ld.shared.u16 %0, [%1];" : "=r"(v) : "r"(addr) : "memory");
  return __uint_as_float(v << 16);
}
__device__ __forceinline__ unsigned ld_flag(const unsigned* f) {
  unsigned v;
  asm volatile("ld.relaxed.gpu.global.u32 %0, [%1];" : "=r"(v) : "l"(f) : "memory");
  return v;
}
__device__ __forceinline__ float gelu2(float v, float k1) {
  const float p = fmaf(v * v, k1, 0.7978845608028654f);
  float t;
  asm("tanh.approx.f32 %0, %1;" : "=f"(t) : "f"(v * p));
  return fmaf(v, t, v);
}


__device__ __forceinline__ void release_slot(uint32_t bar, uint32_t peer_bar, int s, bool pred, bool pred_a) {
  if (pred_a) mbar_arrive(bar + 256 + s * 8);
  if (pred) { mbar_arrive(bar + 64 + s * 8); mbar_arrive_remote(peer_bar + 64 + s * 8); }
}
__device__ __forceinline__ void mma_round(float (&acc)[64], uint64_t dw, uint64_t dx, uint32_t bar, uint32_t peer_bar, uint32_t parity,
                                          uint32_t& ok, int nblk, uint32_t accumulate, bool rel_lo, bool rel_hi, bool rel_a,
                                          bool short_last, int next_bar) {
#pragma unroll
  for (int s = 0; s < 8; s++) {
    if (s >= 6 && s >= nblk) break;
    if (!ok) mbar_wait(bar + s * 8, parity);
    const uint64_t w = dw + s * (kBSlot >> 4), x = dx + s * (kASlot >> 4);
    if (s == 7 && short_last) {
      wg_fence();
      wgmma_t128(acc, w, x, 1u);
      wgmma_t128(acc, w + 128, x + 2, 1u);
      wg_commit();
    } else {
      wg_fence();
      wgmma_t128(acc, w, x, s == 0 ? accumulate : 1u);
      wgmma_t128(acc, w + 128, x + 2, 1u);
      wgmma_t128(acc, w + 256, x + 4, 1u);
      wgmma_t128(acc, w + 384, x + 6, 1u);
      wg_commit();
    }
    if (s == 7 && next_bar) bar_arrive(next_bar, 256);
    const bool rel = s < 2 ? rel_lo : rel_hi;
    release_slot(bar, peer_bar, (s + 6) & 7, rel, rel && rel_a);
    ok = mbar_test(bar + ((s + 1) & 7) * 8, s == 7 ? parity ^ 1u : parity);
    wg_wait<1>();
  }
}

__device__ __forceinline__ uint32_t stage_addr(uint32_t tile, int w, int lane) {
  const int m = lane >> 3, r7 = lane & 7;
  return tile + ((m >> 1) * 8 + r7) * 128 + (((2 * w + (m & 1)) ^ r7) << 4);
}

__global__ void __cluster_dims__(2, 1, 1) __launch_bounds__(kThreads, 1)
ffn_fused_kernel(const __nv_bfloat16* __restrict__ b1, const __nv_bfloat16* __restrict__ b2, __nv_bfloat16* __restrict__ out,
                 const __grid_constant__ CUtensorMap mX, const __grid_constant__ CUtensorMap mW1,
                 const __grid_constant__ CUtensorMap mW1h, const __grid_constant__ CUtensorMap mH,
                 const __grid_constant__ CUtensorMap mHs, const __grid_constant__ CUtensorMap mW2h) {
  extern __shared__ uint8_t smem_raw[];
  uint32_t base = (smem_u32(smem_raw) + 1023u) & ~1023u;
  asm volatile("mov.u32 %0, %0;" : "+r"(base));
  const uint32_t sA = base + kOffA, sB = base + kOffB, sStage = base + kOffStage;
  const uint32_t bar_full = base + kOffBar;
  const uint32_t bar_empty = bar_full + 64;
  const uint32_t bar_staged = bar_full + 128;
  const uint32_t bar_stfree = bar_full + 224;
  const uint32_t bar_bias = bar_full + 232;
  const uint32_t bar_emptyA = bar_full + 256;
  const uint32_t sBias = bar_full + 320;
  const uint32_t bar_hf = bar_full + 832;
  const int warp = __shfl_sync(0xffffffff, threadIdx.x >> 5, 0);
  const int lane = threadIdx.x & 31;

  int grp, j;
  {
    const int c = blockIdx.x >> 1;
    int gpc;
    if (c < 4) { gpc = 0; j = 4 + c; }
    else if (c < 36) { gpc = (c - 4) & 7; j = (c - 4) >> 3; }
    else { gpc = 1 + (c - 36) % 7; j = 4 + (c - 36) / 7; }
    grp = 2 * gpc + (blockIdx.x & 1);
  }
  const int row0 = grp * 128;
  const uint32_t rank = blockIdx.x & 1;

  constexpr int kEarly = 2;
  {
    uint32_t tid_opaque = threadIdx.x;
    asm volatile("" : "+r"(tid_opaque));
    if (__builtin_expect(tid_opaque == 256, 1)) {
#pragma unroll
      for (int i = 0; i < 8; i++) mbar_init(bar_full + i * 8, 1);
      asm volatile("fence.mbarrier_init.release.cluster;" ::: "memory");
#pragma unroll
      for (int kb = 0; kb < kEarly; kb++) {
        mbar_expect_tx(bar_full + kb * 8, kASlot + kBSlot);
        tma_load(sA + kb * kASlot, &mX, bar_full + kb * 8, kb * 64, row0);
        tma_load(sB + kb * kBSlot, &mW1, bar_full + kb * 8, 192 * j, kb * 64);
      }
    }
    __syncwarp();
  }

  if (warp == 8) {
    const int wcol = 192 * j;
    bar_arrive(1, kThreads - 32);
    cluster_arrive();
    if (elect_one()) {
#pragma unroll
      for (int kb = kEarly; kb < 8; kb++) {
        mbar_expect_tx(bar_full + kb * 8, kASlot + kBSlot);
        tma_load(sA + kb * kASlot, &mX, bar_full + kb * 8, kb * 64, row0);
        tma_load(sB + kb * kBSlot, &mW1, bar_full + kb * 8, wcol, kb * 64);
      }
    }
    __syncwarp();
    cluster_wait();
#pragma unroll 1
    for (int it = 8; it < 24; it++) {
      const int s = it & 7, t = it >> 3;
      mbar_wait(bar_empty + s * 8, (t - 1) & 1);
      if (elect_one()) {
        mbar_expect_tx(bar_full + s * 8, kBSlot);
        tma_load_pair(sB + s * kBSlot + rank * 4096, &mW1h, bar_full + s * 8, wcol + 64 * t, s * 64 + rank * 32);
      }
      __syncwarp();
    }
    {
      uint32_t off = 0, par = 0;
      int col = rank * 32;
#pragma unroll 1
      for (int q = 0; q < 22; q++) {
        if (q == 8) col = 64 + rank * 32;
        if (q == 15) col = 128 + rank * 32;
        mbar_wait(bar_empty + off, par);
        if (elect_one()) {
          mbar_expect_tx(bar_full + off, kASlot + kBSlot);
          tma_load_pair(sB + off * (kBSlot / 8) + rank * 4096, &mW2h, bar_full + off, j * 64, col);
        }
        __syncwarp();
        col += 192;
        off += 8;
        if (off == 64) { off = 0; par ^= 1; }
      }
    }
  } else if (warp == 9) {
    if (elect_one()) {
#pragma unroll
      for (int i = 0; i < 8; i++) mbar_init(bar_empty + i * 8, 8);
      mbar_init(bar_bias, 1);
#pragma unroll
      for (int i = 0; i < 6; i++) mbar_init(bar_staged + i * 8, 4);
      mbar_init(bar_stfree, 1);
#pragma unroll
      for (int i = 0; i < 8; i++) mbar_init(bar_emptyA + i * 8, 4);
#pragma unroll
      for (int i = 0; i < 24; i++) mbar_init(bar_hf + i * 8, 1);
      asm volatile("fence.mbarrier_init.release.cluster;" ::: "memory");
    }
    __syncwarp();
    bar_arrive(6, 64);
    cluster_arrive();
    bar_sync(1, kThreads - 32);
    cluster_wait();
    uint32_t off = 0, par = 0;
#pragma unroll 1
    for (int t = 0; t < 3; t++) {
      const int nq = t == 0 ? 8 : 7;
      int col = t * 64;
#pragma unroll 1
      for (int i = 0; i < nq; i++) {
        const bool published = mbar_test(bar_hf + (t * 8 + i) * 8, 0), vacant = mbar_test(bar_emptyA + off, par);
        if (!published) mbar_wait(bar_hf + (t * 8 + i) * 8, 0);
        if (i == 0) asm volatile("fence.proxy.async.global;" ::: "memory");
        if (!vacant) mbar_wait(bar_emptyA + off, par);
        if (elect_one()) tma_load(sA + off * (kASlot / 8), &mH, bar_full + off, col, row0);
        __syncwarp();
        col += 192;
        off += 8;
        if (off == 64) { off = 0; par ^= 1; }
      }
    }
  } else if (warp == 11) {
    cluster_arrive();
    bar_sync(1, kThreads - 32);
    cluster_wait();
    const unsigned target = (ld_flag(&g_done) >> 7) + 1u;
#pragma unroll 1
    for (int t = 0; t < 3; t++) {
      const uint32_t want = t == 0 ? 0xffu : 0x7fu;
      const unsigned* f = &g_flags[(grp * 3 + t) * 8 + (lane & 7)];
      uint32_t seen = 0;
      unsigned v0 = ld_flag(f);
      __nanosleep(60);
      unsigned v1 = ld_flag(f);
#pragma unroll 1
      for (uint32_t spins = 0;; spins++) {
        uint32_t m = __ballot_sync(0xffffffff, (int)(v0 - target) >= 0) & want;
        if (lane < 8 && (((m & ~seen) >> lane) & 1u)) mbar_arrive(bar_hf + (t * 8 + lane) * 8);
        seen |= m;
        if (seen == want) break;
        v0 = ld_flag(f);
        m = __ballot_sync(0xffffffff, (int)(v1 - target) >= 0) & want;
        if (lane < 8 && (((m & ~seen) >> lane) & 1u)) mbar_arrive(bar_hf + (t * 8 + lane) * 8);
        seen |= m;
        if (seen == want) break;
        v1 = ld_flag(f);
        if (spins > kFlagSpins) __trap();
      }
    }
  } else if (warp == 10) {
    cluster_arrive();
    {
      uint32_t v[4];
#pragma unroll
      for (int i = 0; i < 3; i++) {
        const int c = 192 * j + 64 * i + 2 * lane;
        v[i] = c < kF ? __ldg(reinterpret_cast<const uint32_t*>(b1 + c)) : 0u;
      }
      v[3] = __ldg(reinterpret_cast<const uint32_t*>(b2 + j * 64 + 2 * lane));
#pragma unroll
      for (int i = 0; i < 4; i++) asm volatile("st.shared.u32 [%0], %1;" ::"r"(sBias + i * 128 + lane * 4), "r"(v[i]) : "memory");
      bar_sync(6, 64);
      if (lane == 0) mbar_arrive(bar_bias);
    }
    cluster_wait();
    const int nt = j < 7 ? 3 : 1;
#pragma unroll 1
    for (int t = 0; t < nt; t++) {
#pragma unroll 1
      for (int hf = 0; hf < 2; hf++) {
        mbar_wait(bar_staged + (t * 2 + hf) * 8, 0);
        if (elect_one()) {
          tma_store(&mHs, sStage + (t & 1) * kASlot + hf * 8192, (3 * j + t) * 64, row0 + hf * 64);
          asm volatile("cp.async.bulk.commit_group;" ::: "memory");
        }
        __syncwarp();
      }
      if (elect_one()) {
        asm volatile("cp.async.bulk.wait_group 0;" ::: "memory");
        asm volatile("red.relaxed.gpu.global.add.u32 [%0], 1;" ::"l"(&g_flags[(grp * 3 + t) * 8 + j]) : "memory");
        if (t == 0) mbar_arrive(bar_stfree);
      }
      __syncwarp();
    }
  } else {
    const int wg = warp >> 2, w = warp & 3;
    const int my_turn = wg ? 2 : 3, other_turn = wg ? 3 : 2;
    const bool leader = lane == 0;
    float acc[64];
    const uint64_t dx0 = make_desc(sA), dw0 = make_desc(sB);
    const int mcol = 16 * w + (lane >> 2);
    uint32_t peer_bar;
    asm volatile("mapa.shared::cluster.u32 %0, %1, %2;" : "=r"(peer_bar) : "r"(bar_full), "r"(rank ^ 1));
    cluster_arrive();
    bar_sync(1, kThreads - 32);
    cluster_wait();
    const uint32_t zero = blockIdx.y;
#pragma unroll 1
    for (int round = wg; round < 4; round += 2) {
      uint32_t accumulate = 0u;
      if (round < 3) {
        mbar_wait(bar_bias, 0);
        const float c0 = lds_bf16(sBias + round * 128 + mcol * 2), c1 = lds_bf16(sBias + round * 128 + mcol * 2 + 16);
#pragma unroll
        for (int g = 0; g < 16; g++) { acc[4 * g] = c0; acc[4 * g + 1] = c0; acc[4 * g + 2] = c1; acc[4 * g + 3] = c1; }
        accumulate = 1u;
      }
      fence_acc(acc);
      if (round > 0) bar_sync(my_turn, 256);
      uint32_t ok = 0;
      const int last = round == 3 ? 5 : round;
#pragma unroll 1
      for (int rr = round; rr <= last; rr++) {
        mma_round(acc, dw0, dx0, bar_full, peer_bar, rr & 1, ok, rr == 5 ? 6 : 8, accumulate, leader && rr == 4, leader && rr != 5,
                  rr >= 2, rr == 3, rr < 3 ? other_turn : 0);
        accumulate = 1u;
      }
      if (round < 3) release_slot(bar_full, peer_bar, 6, leader, leader && round == 2);
      wg_wait<0>();
      fence_acc(acc);
      if (round == 3) break;
      release_slot(bar_full, peer_bar, 7, leader, leader && round == 2);
      if (round == 2) mbar_wait(bar_stfree, 0);
      const uint32_t sa = stage_addr(sStage + wg * kASlot, w, lane);
      uint32_t dep = 0;
#pragma unroll
      for (int gp = 0; gp < 8; gp++) {
        const float k1 = __uint_as_float(__float_as_uint(0.035677408136300125f) | (dep & zero));
        uint32_t p[4];
#pragma unroll
        for (int h = 0; h < 2; h++) {
          const int g = 2 * gp + h;
          p[2 * h] = pack_bf16(gelu2(acc[4 * g], k1), gelu2(acc[4 * g + 1], k1));
          p[2 * h + 1] = pack_bf16(gelu2(acc[4 * g + 2], k1), gelu2(acc[4 * g + 3], k1));
        }
        dep = p[3];
        if (gp == 4) {
          fence_async_smem();
          __syncwarp();
          if (leader) mbar_arrive(bar_staged + round * 16);
        }
        stmatrix_x4_trans(sa + gp * 2048, p[0], p[1], p[2], p[3]);
        __syncwarp();
      }
      fence_async_smem();
      __syncwarp();
      if (leader) mbar_arrive(bar_staged + round * 16 + 8);
    }
    if (wg == 1) {
      const float bias0 = lds_bf16(sBias + 384 + mcol * 2), bias1 = lds_bf16(sBias + 384 + mcol * 2 + 16);
      const uint32_t otile = sA + 7 * kASlot;
      const uint32_t sa = stage_addr(otile, w, lane);
#pragma unroll
      for (int gp = 0; gp < 8; gp++) {
        uint32_t p[4];
#pragma unroll
        for (int h = 0; h < 2; h++) {
          const int g = 2 * gp + h;
          p[2 * h] = pack_bf16(fmaf(acc[4 * g], 0.5f, bias0), fmaf(acc[4 * g + 1], 0.5f, bias0));
          p[2 * h + 1] = pack_bf16(fmaf(acc[4 * g + 2], 0.5f, bias1), fmaf(acc[4 * g + 3], 0.5f, bias1));
        }
        stmatrix_x4_trans(sa + gp * 2048, p[0], p[1], p[2], p[3]);
      }
      bar_sync(4, 128);
      const int t = threadIdx.x & 127, ch = t & 7;
      __nv_bfloat16* optr = out + (size_t)(row0 + (t >> 3)) * kD + j * 64 + ch * 8;
#pragma unroll
      for (int i = 0; i < 8; i++) {
        const int row = 16 * i + (t >> 3);
        const uint4 v = lds128(otile + row * 128 + ((ch ^ (row & 7)) << 4));
        *reinterpret_cast<uint4*>(optr + (size_t)i * 16 * kD) = v;
      }
      if (t == 0) asm volatile("red.relaxed.gpu.global.add.u32 [%0], 1;" ::"l"(&g_done) : "memory");
    }
  }
}

typedef CUresult (*EncodeTiledFn)(CUtensorMap*, CUtensorMapDataType, cuuint32_t, void*, const cuuint64_t*, const cuuint64_t*,
                                  const cuuint32_t*, const cuuint32_t*, CUtensorMapInterleave, CUtensorMapSwizzle,
                                  CUtensorMapL2promotion, CUtensorMapFloatOOBfill);

void encode_2d(EncodeTiledFn fn, CUtensorMap* m, const void* ptr, uint64_t cols, uint64_t rows, uint32_t box_cols, uint32_t box_rows) {
  cuuint64_t dims[2] = {cols, rows};
  cuuint64_t strides[1] = {cols * 2};
  cuuint32_t box[2] = {box_cols, box_rows};
  cuuint32_t es[2] = {1, 1};
  fn(m, CU_TENSOR_MAP_DATA_TYPE_BFLOAT16, 2, const_cast<void*>(ptr), dims, strides, box, es, CU_TENSOR_MAP_INTERLEAVE_NONE,
     CU_TENSOR_MAP_SWIZZLE_128B, CU_TENSOR_MAP_L2_PROMOTION_L2_128B, CU_TENSOR_MAP_FLOAT_OOB_FILL_NONE);
}

}

extern "C" void kernel_launch(void* const* d_in, const int* in_sizes, int n_in, void* d_out, int out_size) {
  (void)in_sizes; (void)n_in; (void)out_size;
  static CUtensorMap mX, mW1, mW1h, mH, mHs, mW2h;
  static const void* cached[3] = {nullptr, nullptr, nullptr};
  if (cached[0] != d_in[0] || cached[1] != d_in[1] || cached[2] != d_in[3]) {
    void* fnp = nullptr;
    cudaDriverEntryPointQueryResult st;
    cudaGetDriverEntryPoint("cuTensorMapEncodeTiled", &fnp, cudaEnableDefault, &st);
    EncodeTiledFn fn = (EncodeTiledFn)fnp;
    void* hptr = nullptr;
    cudaGetSymbolAddress(&hptr, g_h);
    encode_2d(fn, &mX, d_in[0], kD, kM, 64, 128);
    encode_2d(fn, &mW1, d_in[1], kF, kD, 64, 64);
    encode_2d(fn, &mW1h, d_in[1], kF, kD, 64, 32);
    encode_2d(fn, &mH, hptr, kHP, kM, 64, 128);
    encode_2d(fn, &mHs, hptr, kHP, kM, 64, 64);
    encode_2d(fn, &mW2h, d_in[3], kD, kF, 64, 32);
    cudaFuncSetAttribute(ffn_fused_kernel, cudaFuncAttributeMaxDynamicSharedMemorySize, kSmemBytes);
    cached[0] = d_in[0]; cached[1] = d_in[1]; cached[2] = d_in[3];
  }
  ffn_fused_kernel<<<128, kThreads, kSmemBytes, cudaStreamPerThread>>>(
      (const __nv_bfloat16*)d_in[2], (const __nv_bfloat16*)d_in[4], (__nv_bfloat16*)d_out, mX, mW1, mW1h, mH, mHs, mW2h);
}
```

```cpp
#include <cuda_runtime.h>
#include <cuda_bf16.h>
#include <cuda.h>
#include <stdint.h>

namespace {

constexpr int kM = 2048, kD = 512, kF = 1376;
constexpr int kHP = 1408;
constexpr int kThreads = 384;
constexpr uint32_t kASlot = 16384;
constexpr uint32_t kBSlot = 8192;
constexpr uint32_t kOffA = 0, kOffB = 8 * kASlot, kOffStage = kOffB + 8 * kBSlot, kOffBar = kOffStage + 2 * kASlot;
constexpr uint32_t kSmemBytes = kOffBar + 1024 + 1024;
constexpr uint32_t kMbarSpins = 1u << 18, kFlagSpins = 1u << 20;

__device__ __align__(1024) __nv_bfloat16 g_h[kM * kHP];
__device__ unsigned g_flags[16 * 3 * 8];
__device__ unsigned g_done;

__device__ __forceinline__ uint32_t smem_u32(const void* p) { return (uint32_t)__cvta_generic_to_shared(p); }
__device__ __forceinline__ void mbar_init(uint32_t bar, uint32_t cnt) {
  asm volatile("mbarrier.init.shared::cta.b64 [%0], %1;" ::"r"(bar), "r"(cnt) : "memory");
}
__device__ __forceinline__ void mbar_expect_tx(uint32_t bar, uint32_t bytes) {
  asm volatile("mbarrier.arrive.expect_tx.shared::cta.b64 _, [%0], %1;" ::"r"(bar), "r"(bytes) : "memory");
}
__device__ __forceinline__ void mbar_arrive(uint32_t bar) {
  asm volatile("mbarrier.arrive.shared::cta.b64 _, [%0];" ::"r"(bar) : "memory");
}
__device__ __forceinline__ void mbar_arrive_remote(uint32_t cluster_addr) {
  asm volatile("mbarrier.arrive.shared::cluster.b64 _, [%0];" ::"r"(cluster_addr) : "memory");
}
__device__ __forceinline__ void mbar_wait(uint32_t bar, uint32_t parity) {
  uint32_t ok;
#pragma unroll 1
  for (uint32_t i = 0; i < kMbarSpins; i++) {
    asm volatile("{\n.reg .pred p;\nmbarrier.try_wait.parity.shared::cta.b64 p, [%1], %2;\nselp.u32 %0, 1, 0, p;\n}"
                 : "=r"(ok) : "r"(bar), "r"(parity) : "memory");
    if (ok) return;
  }
  __trap();
}
__device__ __forceinline__ bool mbar_test(uint32_t bar, uint32_t parity) {
  uint32_t ok;
  asm volatile("{\n.reg .pred p;\nmbarrier.test_wait.parity.shared::cta.b64 p, [%1], %2;\nselp.u32 %0, 1, 0, p;\n}"
               : "=r"(ok) : "r"(bar), "r"(parity) : "memory");
  return ok;
}
__device__ __forceinline__ bool elect_one() {
  uint32_t pred;
  asm volatile("{\n.reg .pred p;\nelect.sync _|p, 0xffffffff;\nselp.u32 %0, 1, 0, p;\n}" : "=r"(pred));
  return pred;
}
__device__ __forceinline__ void tma_load(uint32_t dst, const CUtensorMap* map, uint32_t bar, int c0, int c1) {
  asm volatile("cp.async.bulk.tensor.2d.shared::cluster.global.mbarrier::complete_tx::bytes [%0], [%1, {%3, %4}], [%2];"
               ::"r"(dst), "l"(map), "r"(bar), "r"(c0), "r"(c1) : "memory");
}
__device__ __forceinline__ void tma_load_pair(uint32_t dst, const CUtensorMap* map, uint32_t bar, int c0, int c1) {
  asm volatile("cp.async.bulk.tensor.2d.shared::cluster.global.mbarrier::complete_tx::bytes.multicast::cluster [%0], [%1, {%3, %4}], [%2], %5;"
               ::"r"(dst), "l"(map), "r"(bar), "r"(c0), "r"(c1), "h"((uint16_t)3) : "memory");
}
__device__ __forceinline__ void tma_store(const CUtensorMap* map, uint32_t src, int c0, int c1) {
  asm volatile("cp.async.bulk.tensor.2d.global.shared::cta.bulk_group [%0, {%2, %3}], [%1];"
               ::"l"(map), "r"(src), "r"(c0), "r"(c1) : "memory");
}
__device__ __forceinline__ void cluster_arrive() { asm volatile("barrier.cluster.arrive.relaxed.aligned;" ::: "memory"); }
__device__ __forceinline__ void cluster_wait() { asm volatile("barrier.cluster.wait.aligned;" ::: "memory"); }
__device__ __forceinline__ void bar_sync(int id, int n) { asm volatile("bar.sync %0, %1;" ::"r"(id), "r"(n) : "memory"); }
__device__ __forceinline__ void bar_arrive(int id, int n) { asm volatile("bar.arrive %0, %1;" ::"r"(id), "r"(n) : "memory"); }
__device__ __forceinline__ void fence_async_smem() { asm volatile("fence.proxy.async.shared::cta;" ::: "memory"); }
__device__ __forceinline__ void wg_fence() { asm volatile("wgmma.fence.sync.aligned;" ::: "memory"); }
__device__ __forceinline__ void wg_commit() { asm volatile("wgmma.commit_group.sync.aligned;" ::: "memory"); }
template <int N> __device__ __forceinline__ void wg_wait() { asm volatile("wgmma.wait_group.sync.aligned %0;" ::"n"(N) : "memory"); }
__device__ __forceinline__ void fence_acc(float (&d)[64]) {
#pragma unroll
  for (int i = 0; i < 64; i++) asm volatile("" : "+f"(d[i])::"memory");
}
__device__ __forceinline__ uint64_t make_desc(uint32_t addr) {
  return (uint64_t)((addr & 0x3FFFF) >> 4) | ((uint64_t)1 << 16) | ((uint64_t)(1024 >> 4) << 32) | ((uint64_t)1 << 62);
}

__device__ __forceinline__ void wgmma_t128(float (&d)[64], uint64_t da, uint64_t db, uint32_t scale_d) {
  asm volatile("{\n.reg .pred p;\nsetp.ne.b32 p, %66, 0;\n"
      "wgmma.mma_async.sync.aligned.m64n128k16.f32.bf16.bf16 "
      "{%0, %1, %2, %3, %4, %5, %6, %7, %8, %9, %10, %11, %12, %13, %14, %15, "
      "%16, %17, %18, %19, %20, %21, %22, %23, %24, %25, %26, %27, %28, %29, %30, %31, "
      "%32, %33, %34, %35, %36, %37, %38, %39, %40, %41, %42, %43, %44, %45, %46, %47, "
      "%48, %49, %50, %51, %52, %53, %54, %55, %56, %57, %58, %59, %60, %61, %62, %63}, "
      "%64, %65, p, 1, 1, 1, 0;\n}\n"
    : "+f"(d[0]), "+f"(d[1]), "+f"(d[2]), "+f"(d[3]), "+f"(d[4]), "+f"(d[5]), "+f"(d[6]), "+f"(d[7]),
      "+f"(d[8]), "+f"(d[9]), "+f"(d[10]), "+f"(d[11]), "+f"(d[12]), "+f"(d[13]), "+f"(d[14]), "+f"(d[15]),
      "+f"(d[16]), "+f"(d[17]), "+f"(d[18]), "+f"(d[19]), "+f"(d[20]), "+f"(d[21]), "+f"(d[22]), "+f"(d[23]),
      "+f"(d[24]), "+f"(d[25]), "+f"(d[26]), "+f"(d[27]), "+f"(d[28]), "+f"(d[29]), "+f"(d[30]), "+f"(d[31]),
      "+f"(d[32]), "+f"(d[33]), "+f"(d[34]), "+f"(d[35]), "+f"(d[36]), "+f"(d[37]), "+f"(d[38]), "+f"(d[39]),
      "+f"(d[40]), "+f"(d[41]), "+f"(d[42]), "+f"(d[43]), "+f"(d[44]), "+f"(d[45]), "+f"(d[46]), "+f"(d[47]),
      "+f"(d[48]), "+f"(d[49]), "+f"(d[50]), "+f"(d[51]), "+f"(d[52]), "+f"(d[53]), "+f"(d[54]), "+f"(d[55]),
      "+f"(d[56]), "+f"(d[57]), "+f"(d[58]), "+f"(d[59]), "+f"(d[60]), "+f"(d[61]), "+f"(d[62]), "+f"(d[63])
    : "l"(da), "l"(db), "r"(scale_d));
}

__device__ __forceinline__ uint32_t pack_bf16(float lo, float hi) {
  uint32_t r;
  asm("cvt.rn.bf16x2.f32 %0, %1, %2;" : "=r"(r) : "f"(hi), "f"(lo));
  return r;
}
__device__ __forceinline__ void stmatrix_x4_trans(uint32_t addr, uint32_t r0, uint32_t r1, uint32_t r2, uint32_t r3) {
  asm volatile("stmatrix.sync.aligned.m8n8.x4.trans.shared.b16 [%0], {%1, %2, %3, %4};" ::"r"(addr), "r"(r0), "r"(r1), "r"(r2), "r"(r3) : "memory");
}
__device__ __forceinline__ uint4 lds128(uint32_t addr) {
  uint4 v;
  asm volatile("ld.shared.v4.b32 {%0, %1, %2, %3}, [%4];" : "=r"(v.x), "=r"(v.y), "=r"(v.z), "=r"(v.w) : "r"(addr) : "memory");
  return v;
}
__device__ __forceinline__ float lds_bf16(uint32_t addr) {
  uint32_t v;
  asm volatile("ld.shared.u16 %0, [%1];" : "=r"(v) : "r"(addr) : "memory");
  return __uint_as_float(v << 16);
}
__device__ __forceinline__ unsigned ld_flag(const unsigned* f) {
  unsigned v;
  asm volatile("ld.relaxed.gpu.global.u32 %0, [%1];" : "=r"(v) : "l"(f) : "memory");
  return v;
}
__device__ __forceinline__ float gelu2(float v, float k1) {
  const float p = fmaf(v * v, k1, 0.7978845608028654f);
  float t;
  asm("tanh.approx.f32 %0, %1;" : "=f"(t) : "f"(v * p));
  return fmaf(v, t, v);
}


__device__ __forceinline__ void release_slot(uint32_t bar, uint32_t peer_bar, int s, bool pred, bool pred_a) {
  if (pred_a) mbar_arrive(bar + 256 + s * 8);
  if (pred) { mbar_arrive(bar + 64 + s * 8); mbar_arrive_remote(peer_bar + 64 + s * 8); }
}
__device__ __forceinline__ void mma_round(float (&acc)[64], uint64_t dw, uint64_t dx, uint32_t bar, uint32_t peer_bar, uint32_t parity,
                                          uint32_t& ok, int nblk, uint32_t accumulate, bool rel_lo, bool rel_hi, bool rel_a,
                                          bool short_last, int next_bar) {
#pragma unroll
  for (int s = 0; s < 8; s++) {
    if (s >= 6 && s >= nblk) break;
    if (!ok) mbar_wait(bar + s * 8, parity);
    const uint64_t w = dw + s * (kBSlot >> 4), x = dx + s * (kASlot >> 4);
    if (s == 7 && short_last) {
      wg_fence();
      wgmma_t128(acc, w, x, 1u);
      wgmma_t128(acc, w + 128, x + 2, 1u);
      wg_commit();
    } else {
      wg_fence();
      wgmma_t128(acc, w, x, s == 0 ? accumulate : 1u);
      wgmma_t128(acc, w + 128, x + 2, 1u);
      wgmma_t128(acc, w + 256, x + 4, 1u);
      wgmma_t128(acc, w + 384, x + 6, 1u);
      wg_commit();
    }
    if (s == 7 && next_bar) bar_arrive(next_bar, 256);
    const bool rel = s < 2 ? rel_lo : rel_hi;
    release_slot(bar, peer_bar, (s + 6) & 7, rel, rel && rel_a);
    ok = mbar_test(bar + ((s + 1) & 7) * 8, s == 7 ? parity ^ 1u : parity);
    wg_wait<1>();
  }
}

__device__ __forceinline__ uint32_t stage_addr(uint32_t tile, int w, int lane) {
  const int m = lane >> 3, r7 = lane & 7;
  return tile + ((m >> 1) * 8 + r7) * 128 + (((2 * w + (m & 1)) ^ r7) << 4);
}

__global__ void __cluster_dims__(2, 1, 1) __launch_bounds__(kThreads, 1)
ffn_fused_kernel(const __nv_bfloat16* __restrict__ b1, const __nv_bfloat16* __restrict__ b2, __nv_bfloat16* __restrict__ out,
                 const __grid_constant__ CUtensorMap mX, const __grid_constant__ CUtensorMap mW1,
                 const __grid_constant__ CUtensorMap mW1h, const __grid_constant__ CUtensorMap mH,
                 const __grid_constant__ CUtensorMap mHs, const __grid_constant__ CUtensorMap mW2h) {
  extern __shared__ uint8_t smem_raw[];
  uint32_t base = (smem_u32(smem_raw) + 1023u) & ~1023u;
  asm volatile("mov.u32 %0, %0;" : "+r"(base));
  const uint32_t sA = base + kOffA, sB = base + kOffB, sStage = base + kOffStage;
  const uint32_t bar_full = base + kOffBar;
  const uint32_t bar_empty = bar_full + 64;
  const uint32_t bar_staged = bar_full + 128;
  const uint32_t bar_stfree = bar_full + 224;
  const uint32_t bar_bias = bar_full + 232;
  const uint32_t bar_emptyA = bar_full + 256;
  const uint32_t sBias = bar_full + 320;
  const uint32_t bar_hf = bar_full + 832;
  const int warp = __shfl_sync(0xffffffff, threadIdx.x >> 5, 0);
  const int lane = threadIdx.x & 31;

  int grp, j;
  {
    const int c = blockIdx.x >> 1;
    int gpc;
    if (c < 4) { gpc = 0; j = 4 + c; }
    else if (c < 36) { gpc = (c - 4) & 7; j = (c - 4) >> 3; }
    else { gpc = 1 + (c - 36) % 7; j = 4 + (c - 36) / 7; }
    grp = 2 * gpc + (blockIdx.x & 1);
  }
  const int row0 = grp * 128;
  const uint32_t rank = blockIdx.x & 1;

  constexpr int kEarly = 2;
  {
    uint32_t tid_opaque = threadIdx.x;
    asm volatile("" : "+r"(tid_opaque));
    if (__builtin_expect(tid_opaque == 256, 1)) {
#pragma unroll
      for (int i = 0; i < 8; i++) mbar_init(bar_full + i * 8, 1);
      asm volatile("fence.mbarrier_init.release.cluster;" ::: "memory");
#pragma unroll
      for (int kb = 0; kb < kEarly; kb++) {
        mbar_expect_tx(bar_full + kb * 8, kASlot + kBSlot);
        tma_load(sA + kb * kASlot, &mX, bar_full + kb * 8, kb * 64, row0);
        tma_load(sB + kb * kBSlot, &mW1, bar_full + kb * 8, 192 * j, kb * 64);
      }
    }
    __syncwarp();
  }

  if (warp == 8) {
    const int wcol = 192 * j;
    bar_arrive(1, kThreads - 32);
    cluster_arrive();
    if (elect_one()) {
#pragma unroll
      for (int kb = kEarly; kb < 8; kb++) {
        mbar_expect_tx(bar_full + kb * 8, kASlot + kBSlot);
        tma_load(sA + kb * kASlot, &mX, bar_full + kb * 8, kb * 64, row0);
        tma_load(sB + kb * kBSlot, &mW1, bar_full + kb * 8, wcol, kb * 64);
      }
    }
    __syncwarp();
    cluster_wait();
#pragma unroll 1
    for (int it = 8; it < 24; it++) {
      const int s = it & 7, t = it >> 3;
      mbar_wait(bar_empty + s * 8, (t - 1) & 1);
      if (elect_one()) {
        mbar_expect_tx(bar_full + s * 8, kBSlot);
        tma_load_pair(sB + s * kBSlot + rank * 4096, &mW1h, bar_full + s * 8, wcol + 64 * t, s * 64 + rank * 32);
      }
      __syncwarp();
    }
    {
      uint32_t off = 0, par = 0;
      int col = rank * 32;
#pragma unroll 1
      for (int q = 0; q < 22; q++) {
        if (q == 8) col = 64 + rank * 32;
        if (q == 15) col = 128 + rank * 32;
        mbar_wait(bar_empty + off, par);
        if (elect_one()) {
          mbar_expect_tx(bar_full + off, kASlot + kBSlot);
          tma_load_pair(sB + off * (kBSlot / 8) + rank * 4096, &mW2h, bar_full + off, j * 64, col);
        }
        __syncwarp();
        col += 192;
        off += 8;
        if (off == 64) { off = 0; par ^= 1; }
      }
    }
  } else if (warp == 9) {
    if (elect_one()) {
#pragma unroll
      for (int i = 0; i < 8; i++) mbar_init(bar_empty + i * 8, 8);
      mbar_init(bar_bias, 1);
#pragma unroll
      for (int i = 0; i < 6; i++) mbar_init(bar_staged + i * 8, 4);
      mbar_init(bar_stfree, 1);
#pragma unroll
      for (int i = 0; i < 8; i++) mbar_init(bar_emptyA + i * 8, 4);
#pragma unroll
      for (int i = 0; i < 24; i++) mbar_init(bar_hf + i * 8, 1);
      asm volatile("fence.mbarrier_init.release.cluster;" ::: "memory");
    }
    __syncwarp();
    bar_arrive(6, 64);
    cluster_arrive();
    bar_sync(1, kThreads - 32);
    cluster_wait();
    uint32_t off = 0, par = 0;
#pragma unroll 1
    for (int t = 0; t < 3; t++) {
      const int nq = t == 0 ? 8 : 7;
      int col = t * 64;
#pragma unroll 1
      for (int i = 0; i < nq; i++) {
        const bool published = mbar_test(bar_hf + (t * 8 + i) * 8, 0), vacant = mbar_test(bar_emptyA + off, par);
        if (!published) mbar_wait(bar_hf + (t * 8 + i) * 8, 0);
        if (i == 0) asm volatile("fence.proxy.async.global;" ::: "memory");
        if (!vacant) mbar_wait(bar_emptyA + off, par);
        if (elect_one()) tma_load(sA + off * (kASlot / 8), &mH, bar_full + off, col, row0);
        __syncwarp();
        col += 192;
        off += 8;
        if (off == 64) { off = 0; par ^= 1; }
      }
    }
  } else if (warp == 11) {
    cluster_arrive();
    bar_sync(1, kThreads - 32);
    cluster_wait();
    const unsigned target = (ld_flag(&g_done) >> 7) + 1u;
#pragma unroll 1
    for (int t = 0; t < 3; t++) {
      const uint32_t want = t == 0 ? 0xffu : 0x7fu;
      const unsigned* f = &g_flags[(grp * 3 + t) * 8 + (lane & 7)];
      uint32_t seen = 0;
      unsigned v0 = ld_flag(f);
      __nanosleep(60);
      unsigned v1 = ld_flag(f);
#pragma unroll 1
      for (uint32_t spins = 0;; spins++) {
        uint32_t m = __ballot_sync(0xffffffff, (int)(v0 - target) >= 0) & want;
        if (lane < 8 && (((m & ~seen) >> lane) & 1u)) mbar_arrive(bar_hf + (t * 8 + lane) * 8);
        seen |= m;
        if (seen == want) break;
        v0 = ld_flag(f);
        m = __ballot_sync(0xffffffff, (int)(v1 - target) >= 0) & want;
        if (lane < 8 && (((m & ~seen) >> lane) & 1u)) mbar_arrive(bar_hf + (t * 8 + lane) * 8);
        seen |= m;
        if (seen == want) break;
        v1 = ld_flag(f);
        if (spins > kFlagSpins) __trap();
      }
    }
  } else if (warp == 10) {
    cluster_arrive();
    {
      uint32_t v[4];
#pragma unroll
      for (int i = 0; i < 3; i++) {
        const int c = 192 * j + 64 * i + 2 * lane;
        v[i] = c < kF ? __ldg(reinterpret_cast<const uint32_t*>(b1 + c)) : 0u;
      }
      v[3] = __ldg(reinterpret_cast<const uint32_t*>(b2 + j * 64 + 2 * lane));
#pragma unroll
      for (int i = 0; i < 4; i++) asm volatile("st.shared.u32 [%0], %1;" ::"r"(sBias + i * 128 + lane * 4), "r"(v[i]) : "memory");
      bar_sync(6, 64);
      if (lane == 0) mbar_arrive(bar_bias);
    }
    cluster_wait();
    const int nt = j < 7 ? 3 : 1;
#pragma unroll 1
    for (int t = 0; t < nt; t++) {
#pragma unroll 1
      for (int hf = 0; hf < 2; hf++) {
        mbar_wait(bar_staged + (t * 2 + hf) * 8, 0);
        if (elect_one()) {
          tma_store(&mHs, sStage + (t & 1) * kASlot + hf * 8192, (3 * j + t) * 64, row0 + hf * 64);
          asm volatile("cp.async.bulk.commit_group;" ::: "memory");
        }
        __syncwarp();
      }
      if (elect_one()) {
        asm volatile("cp.async.bulk.wait_group 0;" ::: "memory");
        asm volatile("red.relaxed.gpu.global.add.u32 [%0], 1;" ::"l"(&g_flags[(grp * 3 + t) * 8 + j]) : "memory");
        if (t == 0) mbar_arrive(bar_stfree);
      }
      __syncwarp();
    }
  } else {
    const int wg = warp >> 2, w = warp & 3;
    const int my_turn = wg ? 2 : 3, other_turn = wg ? 3 : 2;
    const bool leader = lane == 0;
    float acc[64];
    const uint64_t dx0 = make_desc(sA), dw0 = make_desc(sB);
    const int mcol = 16 * w + (lane >> 2);
    uint32_t peer_bar;
    asm volatile("mapa.shared::cluster.u32 %0, %1, %2;" : "=r"(peer_bar) : "r"(bar_full), "r"(rank ^ 1));
    cluster_arrive();
    bar_sync(1, kThreads - 32);
    cluster_wait();
    const uint32_t zero = blockIdx.y;
    mbar_wait(bar_bias, 0);
    float nb0 = lds_bf16(sBias + wg * 128 + mcol * 2), nb1 = lds_bf16(sBias + wg * 128 + mcol * 2 + 16);
#pragma unroll 1
    for (int round = wg; round < 4; round += 2) {
      uint32_t accumulate = 0u;
      if (round < 3) {
#pragma unroll
        for (int g = 0; g < 16; g++) { acc[4 * g] = nb0; acc[4 * g + 1] = nb0; acc[4 * g + 2] = nb1; acc[4 * g + 3] = nb1; }
        accumulate = 1u;
      }
      fence_acc(acc);
      if (round > 0) bar_sync(my_turn, 256);
      uint32_t ok = 0;
      const int last = round == 3 ? 5 : round;
#pragma unroll 1
      for (int rr = round; rr <= last; rr++) {
        mma_round(acc, dw0, dx0, bar_full, peer_bar, rr & 1, ok, rr == 5 ? 6 : 8, accumulate, leader && rr == 4, leader && rr != 5,
                  rr >= 2, rr == 3, rr < 3 ? other_turn : 0);
        accumulate = 1u;
      }
      if (round < 3) release_slot(bar_full, peer_bar, 6, leader, leader && round == 2);
      wg_wait<0>();
      fence_acc(acc);
      if (round == 3) break;
      release_slot(bar_full, peer_bar, 7, leader, leader && round == 2);
      const uint32_t nb = sBias + min(round + 2, 3) * 128 + mcol * 2;
      nb0 = lds_bf16(nb); nb1 = lds_bf16(nb + 16);
      if (round == 2) mbar_wait(bar_stfree, 0);
      const uint32_t sa = stage_addr(sStage + wg * kASlot, w, lane);
      uint32_t dep = 0;
#pragma unroll
      for (int gp = 0; gp < 8; gp++) {
        const float k1 = __uint_as_float(__float_as_uint(0.035677408136300125f) | (dep & zero));
        uint32_t p[4];
#pragma unroll
        for (int h = 0; h < 2; h++) {
          const int g = 2 * gp + h;
          p[2 * h] = pack_bf16(gelu2(acc[4 * g], k1), gelu2(acc[4 * g + 1], k1));
          p[2 * h + 1] = pack_bf16(gelu2(acc[4 * g + 2], k1), gelu2(acc[4 * g + 3], k1));
        }
        dep = p[3];
        if (gp == 4) {
          fence_async_smem();
          __syncwarp();
          if (leader) mbar_arrive(bar_staged + round * 16);
        }
        stmatrix_x4_trans(sa + gp * 2048, p[0], p[1], p[2], p[3]);
        __syncwarp();
      }
      fence_async_smem();
      __syncwarp();
      if (leader) mbar_arrive(bar_staged + round * 16 + 8);
    }
    if (wg == 1) {
      const float bias0 = nb0, bias1 = nb1;
      const uint32_t otile = sA + 7 * kASlot;
      const uint32_t sa = stage_addr(otile, w, lane);
      const int t = threadIdx.x & 127, ch = t & 7;
      __nv_bfloat16* optr = out + (size_t)(row0 + (t >> 3)) * kD + j * 64 + ch * 8;
#pragma unroll
      for (int hf = 0; hf < 2; hf++) {
#pragma unroll
        for (int gp = 4 * hf; gp < 4 * hf + 4; gp++) {
          uint32_t p[4];
#pragma unroll
          for (int h = 0; h < 2; h++) {
            const int g = 2 * gp + h;
            p[2 * h] = pack_bf16(fmaf(acc[4 * g], 0.5f, bias0), fmaf(acc[4 * g + 1], 0.5f, bias0));
            p[2 * h + 1] = pack_bf16(fmaf(acc[4 * g + 2], 0.5f, bias1), fmaf(acc[4 * g + 3], 0.5f, bias1));
          }
          stmatrix_x4_trans(sa + gp * 2048, p[0], p[1], p[2], p[3]);
        }
        bar_sync(4 + hf, 128);
#pragma unroll
        for (int i = 4 * hf; i < 4 * hf + 4; i++) {
          const int row = 16 * i + (t >> 3);
          const uint4 v = lds128(otile + row * 128 + ((ch ^ (row & 7)) << 4));
          *reinterpret_cast<uint4*>(optr + (size_t)i * 16 * kD) = v;
        }
      }
      if (t == 0) asm volatile("red.relaxed.gpu.global.add.u32 [%0], 1;" ::"l"(&g_done) : "memory");
    }
  }
}

typedef CUresult (*EncodeTiledFn)(CUtensorMap*, CUtensorMapDataType, cuuint32_t, void*, const cuuint64_t*, const cuuint64_t*,
                                  const cuuint32_t*, const cuuint32_t*, CUtensorMapInterleave, CUtensorMapSwizzle,
                                  CUtensorMapL2promotion, CUtensorMapFloatOOBfill);

void encode_2d(EncodeTiledFn fn, CUtensorMap* m, const void* ptr, uint64_t cols, uint64_t rows, uint32_t box_cols, uint32_t box_rows) {
  cuuint64_t dims[2] = {cols, rows};
  cuuint64_t strides[1] = {cols * 2};
  cuuint32_t box[2] = {box_cols, box_rows};
  cuuint32_t es[2] = {1, 1};
  fn(m, CU_TENSOR_MAP_DATA_TYPE_BFLOAT16, 2, const_cast<void*>(ptr), dims, strides, box, es, CU_TENSOR_MAP_INTERLEAVE_NONE,
     CU_TENSOR_MAP_SWIZZLE_128B, CU_TENSOR_MAP_L2_PROMOTION_L2_128B, CU_TENSOR_MAP_FLOAT_OOB_FILL_NONE);
}

}

extern "C" void kernel_launch(void* const* d_in, const int* in_sizes, int n_in, void* d_out, int out_size) {
  (void)in_sizes; (void)n_in; (void)out_size;
  static CUtensorMap mX, mW1, mW1h, mH, mHs, mW2h;
  static const void* cached[3] = {nullptr, nullptr, nullptr};
  if (cached[0] != d_in[0] || cached[1] != d_in[1] || cached[2] != d_in[3]) {
    void* fnp = nullptr;
    cudaDriverEntryPointQueryResult st;
    cudaGetDriverEntryPoint("cuTensorMapEncodeTiled", &fnp, cudaEnableDefault, &st);
    EncodeTiledFn fn = (EncodeTiledFn)fnp;
    void* hptr = nullptr;
    cudaGetSymbolAddress(&hptr, g_h);
    encode_2d(fn, &mX, d_in[0], kD, kM, 64, 128);
    encode_2d(fn, &mW1, d_in[1], kF, kD, 64, 64);
    encode_2d(fn, &mW1h, d_in[1], kF, kD, 64, 32);
    encode_2d(fn, &mH, hptr, kHP, kM, 64, 128);
    encode_2d(fn, &mHs, hptr, kHP, kM, 64, 64);
    encode_2d(fn, &mW2h, d_in[3], kD, kF, 64, 32);
    cudaFuncSetAttribute(ffn_fused_kernel, cudaFuncAttributeMaxDynamicSharedMemorySize, kSmemBytes);
    cached[0] = d_in[0]; cached[1] = d_in[1]; cached[2] = d_in[3];
  }
  ffn_fused_kernel<<<128, kThreads, kSmemBytes, cudaStreamPerThread>>>(
      (const __nv_bfloat16*)d_in[2], (const __nv_bfloat16*)d_in[4], (__nv_bfloat16*)d_out, mX, mW1, mW1h, mH, mHs, mW2h);
}
```
